```python
import torch

def _softmax(x, axis=-1):
    return torch.softmax(x, dim=axis)
def _gelu(x):
    return torch.nn.functional.gelu(x, approximate="tanh")
def _silu(x):
    return torch.nn.functional.silu(x)
def _sigmoid(x):
    return torch.sigmoid(x)
def _layernorm(x, axis=-1, eps=1e-5):
    m = x.mean(dim=axis, keepdim=True)
    v = x.var(dim=axis, keepdim=True, unbiased=False)
    return (x - m) / torch.sqrt(v + eps)
def _scatter_add(tgt, idx, src, axis=0):
    return tgt.clone().index_add_(axis, idx, src)
def _segment_sum(src, seg, n):
    out = torch.zeros((n,) + src.shape[1:], dtype=src.dtype)
    return out.index_add_(0, seg, src)
def _pad(x, pw):
    flat = tuple(v for pair in reversed(pw) for v in pair)
    return torch.nn.functional.pad(x, flat)

kernel_name = 'standalone__attention_interact_autoint__recsys'

def setup_inputs():

    _w = (lambda a: (lambda t: t.to(torch.bfloat16) if t.is_floating_point() else t)(torch.as_tensor(a)))
    B, F = 4096, 100
    D = max(2, (128 // 2) * 2)
    H = 2
    Dh = D // H
    return {
        "e": _w((lambda *s: torch.randn(*s, dtype=torch.bfloat16) * 0.05)(B, F, D).to(float)),
        "wq": _w((lambda *s: torch.randn(*s, dtype=torch.bfloat16) * 1.6)(H, D, Dh).to(float)),
        "wk": _w((lambda *s: torch.randn(*s, dtype=torch.bfloat16) * 1.6)(H, D, Dh).to(float)),
        "wv": _w((lambda *s: torch.randn(*s, dtype=torch.bfloat16) * 0.05)(H, D, Dh).to(float)),
        "wres": _w((lambda *s: torch.randn(*s, dtype=torch.bfloat16) * 0.05)(D, D).to(float)),
    }

def reference(e, wq, wk, wv, wres):
    H, D, Dh = wq.shape[0], wq.shape[1], wq.shape[2]
    B, F = e.shape[0], e.shape[1]
    q = torch.einsum('bfd,hdk->bhfk', e, wq)
    k = torch.einsum('bfd,hdk->bhfk', e, wk)
    v = torch.einsum('bfd,hdk->bhfk', e, wv)
    scale = float(Dh) ** -0.5
    scores = torch.einsum('bhfk,bhgk->bhfg', q, k) * scale
    attn = _softmax(scores, axis=-1)
    attn = (lambda x, dt: x.to(dt))(attn, v.dtype)
    ctx = torch.einsum('bhfg,bhgk->bhfk', attn, v)
    ctx = (lambda x, *d: x.permute(*d))(ctx, 0, 2, 1, 3).reshape(B, F, H * Dh)
    res = torch.einsum('bfd,de->bfe', e, wres)
    out = ctx + res
    mask = (lambda x, dt: x.to(dt))(out > 0, out.dtype)
    return out * mask
```

```cpp
#include <cuda_runtime.h>
#include <cuda_bf16.h>
#include <cuda.h>
#include <stdint.h>

#define KNOB(name, val) constexpr int name = val
#define QPRE 8
#define CHAINS 2
#define SB 7
#define LOCK 0
#define TK 2
#define TQ 0
#define TV 2
#define TR_ 2
#define TIEV 1
#define RA0 144
#define RA1 176
#define RB 96
#define WORD 0x04213
#define E1W 5
#define PFX 6
#define EARLY 7
#define XD 2
#define SPE 2
#define PVF 0
#define TP 0
#define CAR 0
#define OPQ 0
#define NEP 1
#define NSP 0
#define RD 0
#define B0S 1
#define JA 2
#define JB 6
#define JC 10
#define NS0 1
#define CLAIM 1

#define TRI()
#define TR(k)
#define TRX 0
#define TRDUMP()

#define PS(k)
#define PW(k)
#define PK(cond, k)
namespace {

constexpr int kB = 4096, kF = 100, kD = 128;
constexpr int kStages = 5;
constexpr int kServe = 1, kClaim = 2;
constexpr int kEHalf = 104 * 128;
constexpr int kEStage = 2 * kEHalf;
constexpr int kQOff = kStages * kEStage;
constexpr int kKOff = kQOff + 16384;
constexpr int kPOff = kKOff + 13312;
constexpr int kPGrp = 13 * 128;
constexpr int kPBuf = 13 * kPGrp;
constexpr int kOOff = kPOff + 44032;
constexpr int kBarOff = kOOff + 13312;
constexpr int kTrashOff = kBarOff + 128;
constexpr int kSumOff = kTrashOff + 512;
constexpr int kZeroOff = kSumOff + 128;
constexpr int kCntOff = kZeroOff + 16;
constexpr int kTrOff = kZeroOff + 128;
constexpr int kSmemBytes = kTrOff + TRX;
static_assert(kQOff % 1024 == 0 && kKOff % 1024 == 0 && kPOff % 1024 == 0 && kOOff % 1024 == 0 &&
              2 * kPBuf <= 44032 && kSmemBytes <= 232448, "smem layout");

enum { BAR_T1 = 1, BAR_X = 2, BAR_QE = 4, BAR_PF = 6, BAR_O = 8, BAR_B = 9, BAR_W = 10, BAR_SP = 11, BAR_OF = 13, BAR_D = 14 };

__device__ unsigned g_claim[256];

__device__ __forceinline__ uint32_t smem_u32(const void* p) { return (uint32_t)__cvta_generic_to_shared(p); }

__device__ __forceinline__ void wg_fence() { asm volatile("wgmma.fence.sync.aligned;\n" ::: "memory"); }
__device__ __forceinline__ void wg_commit() { asm volatile("wgmma.commit_group.sync.aligned;\n" ::: "memory"); }
template <int N> __device__ __forceinline__ void wg_wait() { asm volatile("wgmma.wait_group.sync.aligned %0;\n" ::"n"(N) : "memory"); }
__device__ __forceinline__ void fence_async() { asm volatile("fence.proxy.async.shared::cta;\n" ::: "memory"); }
__device__ __forceinline__ void bar_sync(int id, int n) { asm volatile("bar.sync %0, %1;\n" ::"r"(id), "r"(n) : "memory"); }
__device__ __forceinline__ void bar_arrive(int id, int n) { asm volatile("bar.arrive %0, %1;\n" ::"r"(id), "r"(n) : "memory"); }

#define ACC48_REGS "%0,%1,%2,%3,%4,%5,%6,%7,%8,%9,%10,%11,%12,%13,%14,%15,%16,%17,%18,%19,%20,%21,%22,%23,%24,%25," \
                   "%26,%27,%28,%29,%30,%31,%32,%33,%34,%35,%36,%37,%38,%39,%40,%41,%42,%43,%44,%45,%46,%47"
#define ACC_REGS "{" ACC48_REGS ",%48,%49,%50,%51}"
#define ACC48_OPS(c, d)                                                                                      \
  c(d[0]), c(d[1]), c(d[2]), c(d[3]), c(d[4]), c(d[5]), c(d[6]), c(d[7]), c(d[8]), c(d[9]), c(d[10]),        \
  c(d[11]), c(d[12]), c(d[13]), c(d[14]), c(d[15]), c(d[16]), c(d[17]), c(d[18]), c(d[19]), c(d[20]),        \
  c(d[21]), c(d[22]), c(d[23]), c(d[24]), c(d[25]), c(d[26]), c(d[27]), c(d[28]), c(d[29]), c(d[30]),        \
  c(d[31]), c(d[32]), c(d[33]), c(d[34]), c(d[35]), c(d[36]), c(d[37]), c(d[38]), c(d[39]), c(d[40]),        \
  c(d[41]), c(d[42]), c(d[43]), c(d[44]), c(d[45]), c(d[46]), c(d[47])
#define ACC_OPS(c, d) ACC48_OPS(c, d), c(d[48]), c(d[49]), c(d[50]), c(d[51])

template <int N = 104>
__device__ __forceinline__ void fence_acc(float (&d)[52]) {
  if constexpr (N == 104) asm volatile("" : ACC_OPS("+f", d)::"memory");
  else asm volatile("" : ACC48_OPS("+f", d)::"memory");
}

template <int N, int ACC>
__device__ __forceinline__ void mma_rs(float (&d)[52], uint32_t a0, uint32_t a1, uint32_t a2, uint32_t a3, uint64_t db) {
  if constexpr (N == 104 && ACC) {
    asm volatile("wgmma.mma_async.sync.aligned.m64n104k16.f32.bf16.bf16 " ACC_REGS
                 ", {%52,%53,%54,%55}, %56, %57, 1, 1, 0;\n"
                 : ACC_OPS("+f", d)
                 : "r"(a0), "r"(a1), "r"(a2), "r"(a3), "l"(db), "n"(ACC & 1));
  } else if constexpr (N == 104) {
    asm volatile("wgmma.mma_async.sync.aligned.m64n104k16.f32.bf16.bf16 " ACC_REGS
                 ", {%52,%53,%54,%55}, %56, 0, 1, 1, 0;\n"
                 : ACC_OPS("=f", d)
                 : "r"(a0), "r"(a1), "r"(a2), "r"(a3), "l"(db));
  } else if constexpr (ACC) {
    asm volatile("wgmma.mma_async.sync.aligned.m64n96k16.f32.bf16.bf16 {" ACC48_REGS
                 "}, {%48,%49,%50,%51}, %52, %53, 1, 1, 0;\n"
                 : ACC48_OPS("+f", d)
                 : "r"(a0), "r"(a1), "r"(a2), "r"(a3), "l"(db), "n"(ACC & 1));
  } else {
    asm volatile("wgmma.mma_async.sync.aligned.m64n96k16.f32.bf16.bf16 {" ACC48_REGS
                 "}, {%48,%49,%50,%51}, %52, 0, 1, 1, 0;\n"
                 : ACC48_OPS("=f", d)
                 : "r"(a0), "r"(a1), "r"(a2), "r"(a3), "l"(db));
  }
}
template <bool ACC>
__device__ __forceinline__ void mma_ss(float (&d)[52], uint64_t da, uint64_t db) {
  if constexpr (ACC) {
    asm volatile("wgmma.mma_async.sync.aligned.m64n104k16.f32.bf16.bf16 " ACC_REGS ", %52, %53, 1, 1, 1, 0, 0;\n"
                 : ACC_OPS("+f", d)
                 : "l"(da), "l"(db));
  } else {
    asm volatile("wgmma.mma_async.sync.aligned.m64n104k16.f32.bf16.bf16 " ACC_REGS ", %52, %53, 0, 1, 1, 0, 0;\n"
                 : ACC_OPS("=f", d)
                 : "l"(da), "l"(db));
  }
}

__device__ __forceinline__ uint64_t desc_sw128(uint32_t saddr) {
  return (uint64_t)((saddr & 0x3FFFF) >> 4) | ((uint64_t)1 << 16) | ((uint64_t)(1024 >> 4) << 32) | ((uint64_t)1 << 62);
}
__device__ __forceinline__ uint64_t desc_p(uint32_t saddr) {
  return (uint64_t)((saddr & 0x3FFFF) >> 4) | ((uint64_t)(128 >> 4) << 16) | ((uint64_t)(kPGrp >> 4) << 32);
}

__device__ __forceinline__ uint32_t pack_bf16(float lo, float hi) {
  uint32_t r;
  asm("cvt.rn.bf16x2.f32 %0, %1, %2;\n" : "=r"(r) : "f"(hi), "f"(lo));
  return r;
}
__device__ __forceinline__ uint32_t pack_bf16_relu(float lo, float hi) {
  uint32_t r;
  asm("cvt.rn.relu.bf16x2.f32 %0, %1, %2;\n" : "=r"(r) : "f"(hi), "f"(lo));
  return r;
}
__device__ __forceinline__ float ex2(float x) {
  float y;
  asm("ex2.approx.ftz.f32 %0, %1;\n" : "=f"(y) : "f"(x));
  return y;
}
__device__ __forceinline__ float rcp(float x) {
  float y;
  asm("rcp.approx.ftz.f32 %0, %1;\n" : "=f"(y) : "f"(x));
  return y;
}
__device__ __forceinline__ void stsm_x4(uint32_t addr, uint32_t r0, uint32_t r1, uint32_t r2, uint32_t r3) {
  asm volatile("stmatrix.sync.aligned.m8n8.x4.shared.b16 [%0], {%1,%2,%3,%4};\n" ::"r"(addr), "r"(r0), "r"(r1), "r"(r2), "r"(r3) : "memory");
}
__device__ __forceinline__ void stsm_x1(uint32_t addr, uint32_t r0) {
  asm volatile("stmatrix.sync.aligned.m8n8.x1.shared.b16 [%0], {%1};\n" ::"r"(addr), "r"(r0) : "memory");
}
__device__ __forceinline__ void stsm_x4_t(uint32_t addr, uint32_t r0, uint32_t r1, uint32_t r2, uint32_t r3) {
  asm volatile("stmatrix.sync.aligned.m8n8.x4.trans.shared.b16 [%0], {%1,%2,%3,%4};\n" ::"r"(addr), "r"(r0), "r"(r1), "r"(r2), "r"(r3) : "memory");
}
__device__ __forceinline__ void stsm_x2_t(uint32_t addr, uint32_t r0, uint32_t r1) {
  asm volatile("stmatrix.sync.aligned.m8n8.x2.trans.shared.b16 [%0], {%1,%2};\n" ::"r"(addr), "r"(r0), "r"(r1) : "memory");
}
__device__ __forceinline__ void ldsm_x4_t(uint32_t addr, uint32_t& r0, uint32_t& r1, uint32_t& r2, uint32_t& r3) {
  asm volatile("ldmatrix.sync.aligned.m8n8.x4.trans.shared.b16 {%0,%1,%2,%3}, [%4];\n" : "=r"(r0), "=r"(r1), "=r"(r2), "=r"(r3) : "r"(addr) : "memory");
}
__device__ __forceinline__ int lds(uint32_t addr) {
  int v;
  asm volatile("ld.shared.u32 %0, [%1];\n" : "=r"(v) : "r"(addr) : "memory");
  return v;
}
__device__ __forceinline__ void mbar_init(uint32_t bar, int count) {
  asm volatile("mbarrier.init.shared::cta.b64 [%0], %1;\n" ::"r"(bar), "r"(count) : "memory");
}
__device__ __forceinline__ void mbar_expect_tx(uint32_t bar, int bytes) {
  asm volatile("mbarrier.arrive.expect_tx.shared::cta.b64 _, [%0], %1;\n" ::"r"(bar), "r"(bytes) : "memory");
}
__device__ __forceinline__ void mbar_wait(uint32_t bar, uint32_t parity) {
  asm volatile(
      "{\n.reg .pred p;\n"
      "WAIT_%=:\n"
      "mbarrier.try_wait.parity.shared::cta.b64 p, [%0], %1;\n"
      "@p bra DONE_%=;\n"
      "bra WAIT_%=;\n"
      "DONE_%=:\n}\n" ::"r"(bar), "r"(parity) : "memory");
}
__device__ __forceinline__ void tma_load_2d(uint32_t dst, const CUtensorMap* tm, int c0, int c1, uint32_t bar) {
  asm volatile("cp.async.bulk.tensor.2d.shared::cluster.global.mbarrier::complete_tx::bytes [%0], [%1, {%3, %4}], [%2];\n" ::"r"(dst),
               "l"(tm), "r"(bar), "r"(c0), "r"(c1) : "memory");
}
__device__ __forceinline__ void tma_store_2d(const CUtensorMap* tm, uint32_t src, int c0, int c1) {
  asm volatile("cp.async.bulk.tensor.2d.global.shared::cta.bulk_group [%0, {%2, %3}], [%1];\n" ::"l"(tm), "r"(src), "r"(c0), "r"(c1) : "memory");
}

template <int N, int FIRST>
__device__ __forceinline__ void proj(float (&acc)[52], const uint32_t (&w)[32], uint64_t de) {
#pragma unroll
  for (int s = 0; s < 8; s++) {
    uint64_t db = de + (uint64_t)(((s >> 2) * kEHalf + (s & 3) * 32) >> 4);
    if (s == 0) mma_rs<N, FIRST>(acc, w[0], w[1], w[2], w[3], db);
    else mma_rs<N, 1>(acc, w[4 * s], w[4 * s + 1], w[4 * s + 2], w[4 * s + 3], db);
  }
}
template <int FIRST>
__device__ __forceinline__ void issue_pv(float (&a)[52], const uint32_t (&vf)[28], uint64_t dp) {
  mma_rs<104, FIRST>(a, vf[0], vf[1], vf[2], vf[3], dp);
#pragma unroll
  for (int s = 1; s < 6; s++) mma_rs<104, 1>(a, vf[4 * s], vf[4 * s + 1], vf[4 * s + 2], vf[4 * s + 3], dp + 16 * s);
  mma_rs<104, 1>(a, vf[24], vf[25], vf[26], vf[27], (dp + 16 * 6) & ~((uint64_t)0x3FFF << 16));
}

__device__ __forceinline__ void sched_barrier() { asm volatile("pmevent 1;\n" ::: "memory"); }

constexpr float kC = 0.125f * 1.4426950408889634f;

__device__ __forceinline__ float quad_sum(float t) {
  t += __shfl_xor_sync(0xffffffffu, t, 1);
  t += __shfl_xor_sync(0xffffffffu, t, 2);
  return t;
}

__device__ __forceinline__ uint32_t mul_bf16x2(uint32_t a, uint32_t b) {
  uint32_t r;
  asm("mul.rn.bf16x2 %0, %1, %2;\n" : "=r"(r) : "r"(a), "r"(b));
  return r;
}
__device__ __forceinline__ bool out_of_range(float t) { return !(t >= 0x1p-30f && t <= 0x1p30f); }
template <int O, bool SUB>
__device__ __forceinline__ float set_exp(const float (&s)[52], uint32_t (&p)[13], bool tail_invalid, float m) {
  float t0, t1;
#pragma unroll
  for (int j = 0; j < 13; j++) {
    const int jj = (j + 12) % 13;
    float x = ex2(SUB ? s[4 * jj + O] - m : s[4 * jj + O]), y = ex2(SUB ? s[4 * jj + O + 1] - m : s[4 * jj + O + 1]);
    if (jj == 12 && tail_invalid) { x = 0.f; y = 0.f; }
    p[jj] = pack_bf16(x, y);
    if (CHAINS == 1) { if (j == 0) t0 = x + y; else { t0 += x; t0 += y; } }
    else { if (j == 0) { t0 = x; t1 = y; } else { t0 += x; t1 += y; } }
  }
  return CHAINS == 1 ? t0 : t0 + t1;
}
template <int O, int J0, int J1>
__device__ __forceinline__ void part_exp(const float (&s)[52], uint32_t (&p)[13], bool tail_invalid, float& t0, float& t1) {
#pragma unroll
  for (int j = J0; j < J1; j++) {
    const int jj = (j + 12) % 13;
    float x = ex2(s[4 * jj + O]), y = ex2(s[4 * jj + O + 1]);
    if (jj == 12 && tail_invalid) { x = 0.f; y = 0.f; }
    p[jj] = pack_bf16(x, y);
    if (j == 0) { t0 = x; t1 = y; } else { t0 += x; t1 += y; }
  }
}
template <int C>
__device__ __forceinline__ void part_store(const uint32_t (&p)[13], uint32_t iv, uint32_t paddr) {
  if (C < 3) stsm_x4(paddr + C * 512, mul_bf16x2(p[4 * C], iv), mul_bf16x2(p[4 * C + 1], iv), mul_bf16x2(p[4 * C + 2], iv), mul_bf16x2(p[4 * C + 3], iv));
  else stsm_x1(paddr + 1536, mul_bf16x2(p[12], iv));
}
#define PIN(x) asm volatile("" : "+f"(x)::"memory")
struct Q3 { float t, s1, s2, s3; };
__device__ __forceinline__ Q3 q3_start(float t) {
  Q3 q;
  q.t = t;
  q.s1 = __shfl_xor_sync(0xffffffffu, t, 1);
  q.s2 = __shfl_xor_sync(0xffffffffu, t, 2);
  q.s3 = __shfl_xor_sync(0xffffffffu, t, 3);
  return q;
}
__device__ __forceinline__ float q3_end(const Q3& q) { return (q.t + q.s1) + (q.s2 + q.s3); }
template <int O>
__device__ __forceinline__ float set_max(const float (&s)[52], bool tail_invalid) {
  float m = fmaxf(s[O], s[O + 1]);
#pragma unroll
  for (int j = 1; j < 12; j++) m = fmaxf(m, fmaxf(s[4 * j + O], s[4 * j + O + 1]));
  if (!tail_invalid) m = fmaxf(m, fmaxf(s[48 + O], s[49 + O]));
  m = fmaxf(m, __shfl_xor_sync(0xffffffffu, m, 1));
  return fmaxf(m, __shfl_xor_sync(0xffffffffu, m, 2));
}
__device__ __forceinline__ uint32_t inv2(float t) { const float iv = rcp(t); return pack_bf16(iv, iv); }
__device__ __forceinline__ void set_store(const uint32_t (&p)[13], float t, uint32_t paddr) {
  const uint32_t iv = inv2(t);
#pragma unroll
  for (int c = 0; c < 3; c++)
    stsm_x4(paddr + c * 512, mul_bf16x2(p[4 * c], iv), mul_bf16x2(p[4 * c + 1], iv), mul_bf16x2(p[4 * c + 2], iv), mul_bf16x2(p[4 * c + 3], iv));
  stsm_x1(paddr + 1536, mul_bf16x2(p[12], iv));
}
__device__ __forceinline__ void issue_s(float (&acc)[52], uint64_t dq, uint64_t dk) {
  wg_fence();
#pragma unroll
  for (int s = 0; s < 4; s++) {
    if (s == 0) mma_ss<false>(acc, dq, dk);
    else mma_ss<true>(acc, dq + 2 * s, dk + 2 * s);
  }
  wg_commit();
}

struct Params { const uint8_t* w[4]; const uint8_t* e; short n_pairs, n_extra, n_open, streams; int zero; unsigned* claim; long long (*cta)[8]; unsigned (*pro)[16]; };

__global__ void __launch_bounds__(512, 1)
autoint_kernel(const __grid_constant__ Params prm,
               const __grid_constant__ CUtensorMap tm_e0, const __grid_constant__ CUtensorMap tm_e1,
               const __grid_constant__ CUtensorMap tm_q, const __grid_constant__ CUtensorMap tm_k,
               const __grid_constant__ CUtensorMap tm_v, const __grid_constant__ CUtensorMap tm_r,
               const __grid_constant__ CUtensorMap tm_o) {
  extern __shared__ __align__(1024) uint8_t smem[];
  const uint32_t sbase = smem_u32(smem);
  const int tid = threadIdx.x;
  const uint32_t bar_full = sbase + kBarOff;
  const uint32_t bar_w = sbase + kBarOff + 64;
  const int cta = blockIdx.x, stream = cta >> 1, head = cta & 1;
  auto load_r = [&](int i, int row) {
    const uint32_t dst = sbase + (i % kStages) * kEStage, bar = bar_full + 8 * (i % kStages);
    const CUtensorMap* tm = (const CUtensorMap*)((const char*)&tm_e0 + (i & 1) * 128);
    mbar_expect_tx(bar, (i & 1) ? 2 * 96 * 128 : 2 * 104 * 128);
    tma_load_2d(dst, tm, 0, row, bar);
    tma_load_2d(dst + kEHalf, tm, 64, row, bar);
  };
  auto load_w = [&](int m) {
    mbar_expect_tx(bar_w + 8 * m, 16384);
    if (m == 0) tma_load_2d(sbase + kPOff, &tm_q, 0, head * 128, bar_w);
    if (m == 1) tma_load_2d(sbase + kPOff + 22528, &tm_k, 0, head * 128, bar_w + 8);
    if (m == 2) tma_load_2d(sbase + 3 * kEStage, &tm_v, 0, head * 128, bar_w + 16);
    if (m == 3) tma_load_2d(sbase + 4 * kEStage, &tm_r, head * 64, 0, bar_w + 24);
  };
  if (tid == 256) {
    mbar_init(bar_full, 1);
    for (int s = 0; s < 4; s++) mbar_init(bar_w + 8 * s, 1);
    asm volatile("fence.mbarrier_init.release.cluster;\n" ::: "memory");
    fence_async();
    PS(0);
#pragma unroll
    for (int k = 0; k < 5; k++) {
      const int m = (WORD >> (4 * (4 - k))) & 15;
      if (m == 4) load_r(0, stream * 2 * kF); else load_w(m);
    }
    PS(1);
    PW(0); PW(1);
  } else if (tid == 288) {
    for (int s = 1; s < kStages; s++) mbar_init(bar_full + 8 * s, 1);
    asm volatile("fence.mbarrier_init.release.cluster;\n" ::: "memory");
    asm volatile("st.shared.v2.u32 [%0], {%1,%1};\n" ::"r"(sbase + kZeroOff), "r"(0) : "memory");
    fence_async();
  } else if (tid >= 320) {
    if ((PFX & 4) && (tid & 31) == 0) asm volatile("prefetch.tensormap [%0];\n" ::"l"((const char*)&tm_e1 + (tid - 320) * 4) : "memory");
  } else if (tid < 208) {
    if (PFX & 1) asm volatile("prefetch.global.L2 [%0];\n" ::"l"(prm.e + stream * (2 * kF * kD * 2) + tid * 128) : "memory");
  } else if (tid >= 224) {
    if (tid < 250) asm volatile("st.shared.v4.u32 [%0], {%1,%1,%1,%1};\nst.shared.v4.u32 [%0 + 16], {%1,%1,%1,%1};\n"
                                ::"r"(sbase + kPOff + 12 * kPGrp + ((tid - 224) >> 1) * 128 + 64 + (tid & 1) * 32), "r"(0) : "memory");
  } else if (tid < 216) {
    if (PFX & 2) asm volatile("prefetch.global.L2 [%0];\n" ::"l"(prm.w[(cta >> 5) & 3] + (cta & 31) * 1024 + (tid & 7) * 128) : "memory");
  }
  const int wg = __shfl_sync(0xffffffffu, tid >> 7, 0);
  PS(2);
  __syncthreads();
  sched_barrier();
  PS(3);
  const int n_pairs = prm.n_pairs, n_open = prm.n_open, streams = prm.streams;
  const int n_static = 2 * (n_pairs + (stream < prm.n_extra));
  const int n_tiles = n_static + (n_open > 0);
  auto row_of = [&](int i) {
    return i < n_static ? (((i >> 1) * streams + stream) * 2 + (i & 1)) * kF : lds(sbase + kCntOff + 4);
  };
  auto load_e = [&](int i) { load_r(i, row_of(i) + (i & 1) * 4); };
  auto read_count = [&]() {
    int v;
    asm volatile("ld.shared.u32 %0, [%1];\n" : "=r"(v) : "r"(sbase + kCntOff) : "memory");
    return __shfl_sync(0xffffffffu, v, 0);
  };

#define ROLE_IDS()                                                                                     \
  int rtid;                                                                                            \
  asm volatile("mov.u32 %0, %tid.x;\n" : "=r"(rtid));                                                  \
  const int lane = rtid & 31;                                                                          \
  const int warp = __shfl_sync(0xffffffffu, (rtid >> 5) & 3, 0);                                       \
  const uint32_t chunk = ((rtid >> 4) & 6) + ((lane >> 3) & 1);                                        \
  const uint32_t t_off = ((lane >> 4) * 8 + (lane & 7)) * 128 + ((chunk ^ (lane & 7)) << 4)
  auto load_frags = [&](uint32_t (&w)[32], int m, uint32_t addr) {
    mbar_wait(bar_w + 8 * m, 0);
#pragma unroll
    for (int s = 0; s < 8; s++) ldsm_x4_t(addr + s * 2048, w[4 * s], w[4 * s + 1], w[4 * s + 2], w[4 * s + 3]);
  };
  const uint64_t dE0 = desc_sw128(sbase);

  if (wg == 0) {
    asm volatile("setmaxnreg.inc.sync.aligned.u32 %0;\n" ::"n"(RA0));
    ROLE_IDS();
    uint32_t wQ[32], wK[32];
    float acc[52];
    load_frags(wQ, 0, sbase + kPOff + t_off);
#pragma unroll
    for (int i = 0; i < 32; i++) wQ[i] = pack_bf16(__uint_as_float(wQ[i] << 16) * kC, __uint_as_float(wQ[i] & 0xffff0000u) * kC);
    load_frags(wK, 1, sbase + kPOff + 22528 + t_off);
    int n_items = n_static;
    const uint32_t k_addr = sbase + kKOff + t_off, q_addr = sbase + kQOff + t_off, q_hi = q_addr + (lane & 16) * 64;
    uint32_t pk[26];
    auto pack = [&](auto NC) {
      constexpr int N = decltype(NC)::value;
      wg_wait<0>();
      fence_acc<N>(acc);
#pragma unroll
      for (int i = 0; i < N / 4; i++) pk[i] = pack_bf16(acc[2 * i], acc[2 * i + 1]);
    };
    auto publish = [&](int it) {
      const int n = it >= 2 ? 384 : 256;
      bar_arrive(BAR_X, n);
      bar_arrive(BAR_X + 1, n);
    };
    auto store_k = [&](auto NC, int j0, int j1) {
      constexpr int N = decltype(NC)::value;
#pragma unroll
      for (int j = j0; j < j1; j += 2) {
        if (j < 12) stsm_x4_t(k_addr + j * 1024, pk[2 * j], pk[2 * j + 1], pk[2 * j + 2], pk[2 * j + 3]);
        else if (N == 104) stsm_x2_t(k_addr + 12 * 1024, pk[24], pk[25]);
      }
    };
    auto item = [&](auto NC, int it) {
      constexpr int N = decltype(NC)::value;
      const uint64_t dE = dE0 + (uint64_t)(((it % kStages) * kEStage) >> 4);
      auto store_q = [&](int j0, int j1) {
#pragma unroll
        for (int j = j0; j < j1; j += 2) {
          if (j < 8) stsm_x4_t(q_addr + j * 1024, pk[2 * j], pk[2 * j + 1], pk[2 * j + 2], pk[2 * j + 3]);
          else if (j < 12) stsm_x4_t(q_hi + (2 * j - 8) * 1024, pk[2 * j], pk[2 * j + 1], pk[2 * j + 2], pk[2 * j + 3]);
          else if (N == 104) {
            stsm_x4_t(q_hi + 9 * 1024, pk[24], pk[25], pk[24], pk[25]);
            stsm_x4_t(q_hi + 13 * 1024, pk[24], pk[25], pk[24], pk[25]);
          }
        }
      };
      TRI();
      TR(0);
      if (it >= 3) bar_sync(BAR_T1, 256);
      if (it >= 1 && it <= NSP) bar_sync(BAR_SP + 1, 256);
      wg_fence();
      proj<N, TQ>(acc, wQ, dE);
      wg_commit();
      if (it > NEP) {
        fence_async();
        publish(it - 1);
      }
      if (XD == 2 && N == 96 && it == 1) bar_arrive(BAR_X + 1, 256);
      if (N == 104 && it == 0) bar_arrive(BAR_T1, 256);
      TR(1);
      pack(NC);
#pragma unroll
      for (int i = 0; i < N / 4; i++) asm volatile("" : "+r"(pk[i])::"memory");
      sched_barrier();
      TR(2);
      PK(PRO2 == 1 && it < 5, it);
      if (it >= 1) bar_sync(BAR_QE, 256);
      store_q(0, QPRE);
      if (it > NSP) bar_sync(BAR_SP + 1, 256);
      TR(3);
      wg_fence();
      proj<N, TK>(acc, wK, dE + ((OPQ & 1) ? (uint32_t)prm.zero : 0u));
      wg_commit();
      if (SPE == 2 && N == 104 && it == 2) bar_arrive(BAR_B, 256);
      if (RD && N == 96 && it == 1) bar_arrive(BAR_B + 6, 256);
      TR(4);
      store_q(QPRE, 8);
      PK(PRO2 == 1 && it < 5 && it, it + 5);
      if (it + 1 < n_tiles && !(N == 104 && it == 0)) mbar_wait(bar_full + 8 * ((it + 1) % kStages), ((it + 1) / kStages) & 1);
      PK(PRO2 == 1 && it < 5 && it, it + 10);
      if (it >= 1) bar_sync(BAR_QE + 1, 256);
      store_q(8, 14);
      if (CLAIM && N == 96 && it + 1 == n_static) n_items = read_count();
      TR(5);
      pack(NC);
      TR(6);
      store_k(NC, 0, 14);
      if (N == 104 && it == 0 && XD == 2) {
        fence_async();
        bar_arrive(BAR_X, 256);
        PK(PRO2 == 1, 5);
        mbar_wait(bar_full + 8, 0);
        PK(PRO2 == 1, 10);
        bar_sync(BAR_SP, 256);
      } else if (N == 104 && it == 0 && NEP == 0) {
        PK(PRO2 == 1, 5);
        mbar_wait(bar_full + 8, 0);
        PK(PRO2 == 1, 10);
      } else if (N == 104 && it == 0) {
        fence_async();
        bar_arrive(BAR_X, 256);
        if (!XD) bar_arrive(BAR_X + 1, 256);
        PK(PRO2 == 1, 5);
        mbar_wait(bar_full + 8, 0);
        PK(PRO2 == 1, 10);
        if (XD) bar_arrive(BAR_X + 1, 256);
      } else if (it < NEP) {
        fence_async();
        publish(it);
      }
      TR(7);
    };
    mbar_wait(bar_full, 0);
    for (int it = 0;; it += 2) {
      item(std::integral_constant<int, 104>{}, it);
      if (it + 1 == n_items) break;
      item(std::integral_constant<int, 96>{}, it + 1);
      if (it + 2 == n_items) break;
    }
    fence_async();
    publish(n_items - 1);
    TRDUMP();
  } else if (wg == 1) {
    asm volatile("setmaxnreg.inc.sync.aligned.u32 %0;\n" ::"n"(RA1));
    ROLE_IDS();
    uint32_t wV[32], wR[32];
    float acc[52];
    uint32_t vf[28], pl[2];
    asm volatile("ld.volatile.shared.v2.u32 {%0, %1}, [%2];\n" : "=r"(vf[26]), "=r"(vf[27]) : "r"(sbase + kZeroOff) : "memory");
    load_frags(wV, 2, sbase + 3 * kEStage + t_off);
    load_frags(wR, 3, sbase + 4 * kEStage + t_off);
    bar_arrive(BAR_W, 160);
    mbar_wait(bar_full, 0);
    bar_sync(BAR_T1, 256);
    int n_items = n_static;
    const uint32_t o_even = sbase + kOOff + t_off;
    const uint32_t r4 = (lane & 7) + 4;
    const uint32_t o_odd = sbase + kOOff + ((lane >> 4) * 8 + r4) * 128 + ((chunk ^ (r4 & 7)) << 4);
    const uint32_t o_odd_last = sbase + kOOff + ((lane & 4) ? (r4 & 7) : 96 + r4) * 128 + ((chunk ^ (r4 & 7)) << 4);
    const uint64_t dP = desc_p(sbase + kPOff);
    auto store_o = [&](int par, int it) {
      const uint32_t a = par ? o_odd : o_even;
      if (it >= 1) bar_sync(BAR_OF, 160);
#pragma unroll
      for (int j = 0; j < 12; j += 2) stsm_x4_t(a + j * 1024, vf[2 * j], vf[2 * j + 1], vf[2 * j + 2], vf[2 * j + 3]);
      stsm_x2_t(par ? o_odd_last : o_even + 12 * 1024, pl[0], pl[1]);
    };
    auto item = [&](auto NC, auto FC, int it) {
      constexpr int N = decltype(NC)::value, par = N == 96;
      constexpr bool first = decltype(FC)::value;
      const uint64_t dE = dE0 + (uint64_t)(((it % kStages) * kEStage) >> 4);
      TRI();
      TR(0);
      if (!first) {
#pragma unroll
        for (int i = 0; i < 24; i++) asm volatile("" : "+r"(vf[i])::"memory");
        asm volatile("" : "+r"(pl[0]), "+r"(pl[1])::"memory");
        sched_barrier();
        if (it + 1 < n_items) bar_sync(BAR_SP, 256);
      }
      wg_fence();
      proj<N, first ? 0 : TV>(acc, wV, dE);
      wg_commit();
      TR(1);
      if (!first) {
        if (it + 1 < n_items) bar_arrive(BAR_X + 1, 384);
        bar_sync(BAR_PF + par, 384);
        fence_async();
        if (CLAIM && par && it + 3 == n_static) n_items = read_count();
        store_o(par ^ 1, it - 1);
        bar_arrive(BAR_O, 160);
      }
      TR(2);
      wg_wait<0>();
      fence_acc<N>(acc);
      TR(3);
#pragma unroll
      for (int i = 0; i < N / 4; i++) {
        if (TIEV && !first) asm("cvt.rn.bf16x2.f32 %0, %1, %2;\n" : "+r"(vf[i]) : "f"(acc[2 * i + 1]), "f"(acc[2 * i]));
        else vf[i] = pack_bf16(acc[2 * i], acc[2 * i + 1]);
      }
      if (RD && first) bar_sync(BAR_B + 6, 256);
      wg_fence();
      proj<N, TR_>(acc, wR, dE + ((OPQ & 2) ? (uint32_t)prm.zero : 0u));
      wg_commit();
      TR(4);
      if (first) {
        bar_sync(BAR_PF + par, 384);
        fence_async();
        if (SPE) bar_sync(BAR_SP, 256);
        if (SPE == 2) bar_sync(BAR_B, 256);
      }
      wg_fence();
      issue_pv<1>(acc, vf, dP + (uint64_t)((par * kPBuf) >> 4));
      wg_commit();
      TR(5);
      if (it + 3 < n_items) bar_arrive(BAR_T1, 256);
      if (!SPE && first) bar_sync(BAR_SP, 256);
      if (it + 1 < n_items) mbar_wait(bar_full + 8 * ((it + 1) % kStages), ((it + 1) / kStages) & 1);
      wg_wait<0>();
      if (it + 2 < n_items) bar_arrive(BAR_X, 384);
      sched_barrier();
      fence_acc(acc);
      TR(7);
#pragma unroll
      for (int i = 0; i < 24; i++) {
        if (TIEV) asm("cvt.rn.relu.bf16x2.f32 %0, %1, %2;\n" : "+r"(vf[i]) : "f"(acc[2 * i + 1]), "f"(acc[2 * i]));
        else vf[i] = pack_bf16_relu(acc[2 * i], acc[2 * i + 1]);
      }
      pl[0] = pack_bf16_relu(acc[48], acc[49]);
      pl[1] = pack_bf16_relu(acc[50], acc[51]);
    };
    item(std::integral_constant<int, 104>{}, std::true_type{}, 0);
    for (int it = 1;; it += 2) {
      item(std::integral_constant<int, 96>{}, std::false_type{}, it);
      if (it + 1 == n_items) break;
      item(std::integral_constant<int, 104>{}, std::false_type{}, it + 1);
      if (it + 2 == n_items) break;
    }
    store_o((n_items - 1) & 1, n_items - 1);
    bar_arrive(BAR_O, 160);
    TRDUMP();
  } else {
    asm volatile("setmaxnreg.dec.sync.aligned.u32 %0;\n" ::"n"(RB));
    ROLE_IDS();
    const uint64_t dK = desc_sw128(sbase + kKOff);
    float acc[52];
    if (wg == 2) {
      const uint64_t dQ = desc_sw128(sbase + kQOff);
      uint32_t pa = sbase + kPOff + 2 * warp * kPGrp + lane * 16;
      int tail = (lane >> 1) & 1;
      if (rtid == 256) {
        if (E1W == 1 || E1W == 2) mbar_wait(bar_full, 0);
        if (E1W == 4) mbar_wait(bar_w, 0);
        if (E1W == 5) mbar_wait(bar_w + 16, 0);
        if (E1W == 6) mbar_wait(bar_w + 8, 0);
        load_e(1);
        if (E1W == 2) mbar_wait(bar_full + 8, 0);
        if (E1W >= 3) mbar_wait(bar_full, 0);
        load_e(2);
      }
      if (rtid == 320) {
        const int m = max((int)n_open, 1), x = stream % m;
        asm volatile("st.shared.v4.u32 [%0], {%1,%2,%3,%4};\n" ::"r"(sbase + kCntOff), "r"(n_static), "r"((2 * n_pairs * streams + x) * kF),
                     "r"(2 * x + head), "r"((streams - 1 - x) / m) : "memory");
      }
      if (warp == kServe) bar_sync(BAR_W, 160);
      __syncwarp();
      int n_items = n_static;
      for (int it = 0; it < n_items; it++) {
        TRI();
        TR(0);
        bar_sync(BAR_X, it >= 2 ? 384 : 256);
        issue_s(acc, dQ, dK);
        if (XD == 2 || it >= 1) bar_arrive(BAR_SP, 256);
        if (warp == kServe && lane == 0 && it + 3 < n_tiles) load_e(it + 3);
        if (CLAIM && it + 1 == n_static) n_items = read_count();
        TR(1);
        wg_wait<0>();
        if (it + 1 < n_items) bar_arrive(BAR_QE, 256);
        sched_barrier();
        fence_acc(acc);
        TR(2);
        PK(PRO2 == 2 && it < 5, it);
        uint32_t p0[13], p1[13];
        float t0, t1, u0, u1;
        part_exp<0, 0, 13>(acc, p0, tail, t0, u0);
        part_exp<2, 0, JA>(acc, p1, tail, t1, u1);
        t0 += u0;
        u0 = __shfl_xor_sync(0xffffffffu, t0, 1);
        PIN(t1); PIN(u1);
        sched_barrier();
        part_exp<2, JA, JB>(acc, p1, tail, t1, u1);
        PIN(t1); PIN(u1);
        if (SB & 1) sched_barrier();
        t0 += u0;
        u0 = __shfl_xor_sync(0xffffffffu, t0, 2);
        sched_barrier();
        part_exp<2, JB, JC>(acc, p1, tail, t1, u1);
        PIN(t1); PIN(u1);
        if (SB & 2) sched_barrier();
        t0 += u0;
        const uint32_t i0 = inv2(t0);
        part_exp<2, JC, 13>(acc, p1, tail, t1, u1);
        part_store<0>(p0, i0, pa);
        if (NS0 > 1) part_store<1>(p0, i0, pa);
        const Q3 q1 = q3_start(t1 + u1);
        sched_barrier();
        if (NS0 <= 1) part_store<1>(p0, i0, pa);
        part_store<2>(p0, i0, pa);
        part_store<3>(p0, i0, pa);
        if (SB & 4) sched_barrier();
        t1 = q3_end(q1);
        if (__any_sync(0xffffffffu, out_of_range(t0) || out_of_range(t1))) {
          set_store(p0, quad_sum(set_exp<0, true>(acc, p0, tail, set_max<0>(acc, tail))), pa);
          t1 = quad_sum(set_exp<2, true>(acc, p1, tail, set_max<2>(acc, tail)));
        }
        set_store(p1, t1, pa + kPGrp);
        PK(PRO2 == 2 && it < 5, it + 5);
        bar_arrive(BAR_PF + (it & 1), 384);
        TR(6);
        pa += (it & 1) ? -kPBuf : kPBuf;
        tail ^= 1;
      }
    } else {
      const uint64_t dQ = desc_sw128(sbase + kQOff + 8192);
      const bool server = warp == kServe;
      auto serve = [&](int it) {
        bar_sync(BAR_O, 160);
        if (lane == 0) {
          fence_async();
          tma_store_2d(&tm_o, sbase + kOOff, head * 64, row_of(it));
          asm volatile("cp.async.bulk.commit_group;\n" ::: "memory");
        }
        __syncwarp();
      };
      auto release_o = [&]() {
        if (lane == 0) asm volatile("cp.async.bulk.wait_group.read 0;\n" ::: "memory");
        __syncwarp();
        bar_arrive(BAR_OF, 160);
      };
      uint32_t pa = sbase + kPOff + (8 + warp) * kPGrp + lane * 16;
      const uint32_t trash = sbase + kTrashOff + lane * 16;
      const uint32_t pd = sbase + kPOff + 12 * kPGrp + (3 * warp + (lane >> 3)) * 128 + (lane & 7) * 16 + ((lane >> 2) & 1) * kPBuf;
      const bool exists = lane < 24 || warp == 3;
      uint32_t pd0 = exists && !(lane & 4) ? pd : trash, pd1 = exists && (lane & 4) ? pd : trash;
      const uint32_t sum_addr = sbase + kSumOff + (lane >> 2) * 16;
      int tail = (lane >> 1) & 1, other = lane >> 4;
      int n_items = n_static;
      uint32_t ticket = 1;
      for (int it = 0; it < n_items; it++) {
        TRI();
        TR(0);
        bar_sync(BAR_X + 1, it >= 2 ? 384 : 256);
        issue_s(acc, dQ, dK);
        if (it + 1 < n_items) bar_arrive(BAR_SP + 1, 256);
        if (CLAIM && it + 2 == n_static) n_items = read_count();
        TR(1);
        wg_wait<0>();
        if (it + 1 < n_items) bar_arrive(BAR_QE + 1, 256);
        if (server && it >= 2) serve(it - 2);
        if (CLAIM && ticket == 0) asm volatile("st.shared.u32 [%0], %1;\n" ::"r"(sbase + kCntOff), "r"(n_static + 1) : "memory");
        if (LOCK) bar_sync(BAR_B, 256);
        sched_barrier();
        fence_acc(acc);
        TR(2);
        PK(PRO2 == 2 && it < 5, it + 10);
        uint32_t p0[13], d[4];
        float td;
        auto d_exp = [&](auto WC, auto SC, float m) {
          constexpr int W = decltype(WC)::value;
          constexpr bool SUB = decltype(SC)::value;
          float x[8];
#pragma unroll
          for (int k = 0; k < (W == 3 ? 8 : 6); k++) {
            const float v = acc[4 * (3 * W + (k >> 1)) + 2 + (k & 1)];
            x[k] = ex2(SUB ? v - m : v);
          }
          td = ((x[0] + x[1]) + (x[2] + x[3])) + (x[4] + x[5]);
          if (W == 3) {
            if (tail) { x[6] = 0.f; x[7] = 0.f; }
            td += x[6] + x[7];
            d[3] = pack_bf16(x[6], x[7]);
          } else d[3] = 0;
#pragma unroll
          for (int k = 0; k < 3; k++) d[k] = pack_bf16(x[2 * k], x[2 * k + 1]);
        };
        auto d_exp_w = [&](auto SC, float m) {
          if (warp == 0) d_exp(std::integral_constant<int, 0>{}, SC, m);
          else if (warp == 1) d_exp(std::integral_constant<int, 1>{}, SC, m);
          else if (warp == 2) d_exp(std::integral_constant<int, 2>{}, SC, m);
          else d_exp(std::integral_constant<int, 3>{}, SC, m);
        };
        d_exp_w(std::false_type{}, 0.f);
        const Q3 qd = q3_start(td);
        float t0 = set_exp<0, false>(acc, p0, tail, 0.f);
        td = q3_end(qd);
        if ((lane & 3) == 0) asm volatile("st.shared.f32 [%0], %1;\n" ::"r"(sum_addr + warp * 4), "f"(td) : "memory");
        const Q3 q0 = q3_start(t0);
        bar_sync(BAR_D, 128);
        float4 u;
        asm volatile("ld.shared.v4.f32 {%0,%1,%2,%3}, [%4];\n" : "=f"(u.x), "=f"(u.y), "=f"(u.z), "=f"(u.w) : "r"(sum_addr) : "memory");
        t0 = q3_end(q0);
        set_store(p0, t0, pa);
        td = (u.x + u.y) + (u.z + u.w);
        if (__any_sync(0xffffffffu, out_of_range(t0) || (!other && out_of_range(td)))) {
          set_store(p0, quad_sum(set_exp<0, true>(acc, p0, tail, set_max<0>(acc, tail))), pa);
          const float m = set_max<2>(acc, tail);
          d_exp_w(std::true_type{}, m);
          td = quad_sum(set_exp<2, true>(acc, p0, tail, m));
        }
        const uint32_t iv = inv2(td);
        stsm_x4(pd0, mul_bf16x2(d[0], iv), mul_bf16x2(d[1], iv), mul_bf16x2(d[2], iv), mul_bf16x2(d[3], iv));
        bar_arrive(BAR_PF + (it & 1), 384);
        if (server && it >= 2) release_o();
        ticket = 1;
        if (CLAIM && it + 4 == n_static && n_open > 0 && rtid == 384 + 32 * kClaim)
          asm volatile("atom.global.inc.u32 %0, [%1], %2;\n" : "=r"(ticket) : "l"(prm.claim + lds(sbase + kCntOff + 8)), "r"(lds(sbase + kCntOff + 12)) : "memory");
        TR(6);
        pa += (it & 1) ? -kPBuf : kPBuf;
        tail ^= 1;
        other ^= 1;
        const uint32_t x = pd0; pd0 = pd1; pd1 = x;
      }
      if (server) {
        serve(n_items - 2);
        release_o();
        serve(n_items - 1);
        if (lane == 0) asm volatile("cp.async.bulk.wait_group.read 0;\n" ::: "memory");
      }
    }
    TRDUMP();
  }
}

typedef CUresult (*EncodeFn)(CUtensorMap*, CUtensorMapDataType, cuuint32_t, void*, const cuuint64_t*, const cuuint64_t*,
                             const cuuint32_t*, const cuuint32_t*, CUtensorMapInterleave, CUtensorMapSwizzle,
                             CUtensorMapL2promotion, CUtensorMapFloatOOBfill);

}

extern "C" void kernel_launch(void* const* d_in, const int* in_sizes, int n_in, void* d_out, int out_size) {
  static EncodeFn encode = nullptr;
  static int num_sms = 0;
  if (!encode) {
    void* fn = nullptr;
    cudaDriverEntryPointQueryResult qres;
    cudaGetDriverEntryPoint("cuTensorMapEncodeTiled", &fn, cudaEnableDefault, &qres);
    encode = (EncodeFn)fn;
    int dev = 0;
    cudaGetDevice(&dev);
    cudaDeviceGetAttribute(&num_sms, cudaDevAttrMultiProcessorCount, dev);
    cudaFuncSetAttribute(autoint_kernel, cudaFuncAttributeMaxDynamicSharedMemorySize, kSmemBytes);
  }
  auto make = [&](void* p, uint64_t cols, uint64_t rows, uint32_t box_rows, CUtensorMapL2promotion promo) {
    CUtensorMap tm;
    cuuint64_t dims[2] = {cols, rows};
    cuuint64_t strides[1] = {cols * 2};
    cuuint32_t box[2] = {64, box_rows};
    cuuint32_t estr[2] = {1, 1};
    encode(&tm, CU_TENSOR_MAP_DATA_TYPE_BFLOAT16, 2, p, dims, strides, box, estr, CU_TENSOR_MAP_INTERLEAVE_NONE,
           CU_TENSOR_MAP_SWIZZLE_128B, promo, CU_TENSOR_MAP_FLOAT_OOB_FILL_NONE);
    return tm;
  };
  const CUtensorMap tm_e0 = make(d_in[0], kD, (uint64_t)kB * kF, 104, CU_TENSOR_MAP_L2_PROMOTION_L2_256B);
  const CUtensorMap tm_e1 = make(d_in[0], kD, (uint64_t)kB * kF, 96, CU_TENSOR_MAP_L2_PROMOTION_L2_256B);
  const CUtensorMap tm_o = make(d_out, kD, (uint64_t)kB * kF, kF, CU_TENSOR_MAP_L2_PROMOTION_NONE);
  const CUtensorMap tm_q = make(d_in[1], 64, 256, 128, CU_TENSOR_MAP_L2_PROMOTION_L2_256B);
  const CUtensorMap tm_k = make(d_in[2], 64, 256, 128, CU_TENSOR_MAP_L2_PROMOTION_L2_256B);
  const CUtensorMap tm_v = make(d_in[3], 64, 256, 128, CU_TENSOR_MAP_L2_PROMOTION_L2_256B);
  const CUtensorMap tm_r = make(d_in[4], 128, 128, 128, CU_TENSOR_MAP_L2_PROMOTION_L2_256B);
  const int grid = (num_sms < 2 ? 2 : num_sms > 256 ? 256 : num_sms) & ~1, streams = grid / 2;
  const int n_pairs = kB / 2 / streams, rem = kB / 2 - n_pairs * streams;
  const bool open = 2 * rem <= streams;
  static unsigned* claim = nullptr;
  if (!claim) cudaGetSymbolAddress((void**)&claim, g_claim);
  void *p_cta = nullptr, *p_pro = nullptr;
  const Params prm = {{(const uint8_t*)d_in[1], (const uint8_t*)d_in[2], (const uint8_t*)d_in[3], (const uint8_t*)d_in[4]},
                      (const uint8_t*)d_in[0], (short)n_pairs, (short)(open ? 0 : rem), (short)(open ? 2 * rem : 0), (short)streams, 0, claim, (long long (*)[8])p_cta, (unsigned (*)[16])p_pro};
  autoint_kernel<<<grid, 512, kSmemBytes>>>(prm, tm_e0, tm_e1, tm_q, tm_k, tm_v, tm_r, tm_o);
}
```

```cpp
#include <cuda_runtime.h>
#include <cuda_bf16.h>
#include <cuda.h>
#include <stdint.h>
#include <type_traits>

namespace {

constexpr int kB = 4096, kF = 100, kD = 128;
constexpr int kStages = 5;
constexpr int kServe = 1, kClaim = 2;
constexpr int kEHalf = 104 * 128;
constexpr int kEStage = 2 * kEHalf;
constexpr int kQOff = kStages * kEStage;
constexpr int kKOff = kQOff + 16384;
constexpr int kPOff = kKOff + 13312;
constexpr int kPGrp = 13 * 128;
constexpr int kPBuf = 13 * kPGrp;
constexpr int kWkOff = kPOff + 22528;
constexpr int kOOff = kPOff + 44032;
constexpr int kBarOff = kOOff + 13312;
constexpr int kTrashOff = kBarOff + 128;
constexpr int kSumOff = kTrashOff + 512;
constexpr int kZeroOff = kSumOff + 128;
constexpr int kCntOff = kZeroOff + 16;
constexpr int kSmemBytes = kZeroOff + 128;
static_assert(kQOff % 1024 == 0 && kKOff % 1024 == 0 && kPOff % 1024 == 0 && kOOff % 1024 == 0 && kWkOff % 1024 == 0 &&
              2 * kPBuf <= 44032 && kWkOff >= kPOff + kPBuf && kWkOff + 16384 <= kOOff && kSmemBytes <= 232448, "smem layout");

enum {
  BAR_T1 = 1,
  BAR_X = 2,
  BAR_QE = 4,
  BAR_PF = 6,
  BAR_O = 8,
  BAR_S2 = 9,
  BAR_W = 10,
  BAR_SP = 11,
  BAR_OF = 13,
  BAR_D = 14,
  BAR_S1 = 15
};

__device__ unsigned g_claim[256];

__device__ __forceinline__ uint32_t smem_u32(const void* p) { return (uint32_t)__cvta_generic_to_shared(p); }

__device__ __forceinline__ void wg_fence() { asm volatile("wgmma.fence.sync.aligned;\n" ::: "memory"); }
__device__ __forceinline__ void wg_commit() { asm volatile("wgmma.commit_group.sync.aligned;\n" ::: "memory"); }
template <int N> __device__ __forceinline__ void wg_wait() { asm volatile("wgmma.wait_group.sync.aligned %0;\n" ::"n"(N) : "memory"); }
__device__ __forceinline__ void fence_async() { asm volatile("fence.proxy.async.shared::cta;\n" ::: "memory"); }
__device__ __forceinline__ void bar_sync(int id, int n) { asm volatile("bar.sync %0, %1;\n" ::"r"(id), "r"(n) : "memory"); }
__device__ __forceinline__ void bar_arrive(int id, int n) { asm volatile("bar.arrive %0, %1;\n" ::"r"(id), "r"(n) : "memory"); }

#define ACC48_REGS "%0,%1,%2,%3,%4,%5,%6,%7,%8,%9,%10,%11,%12,%13,%14,%15,%16,%17,%18,%19,%20,%21,%22,%23,%24,%25," \
                   "%26,%27,%28,%29,%30,%31,%32,%33,%34,%35,%36,%37,%38,%39,%40,%41,%42,%43,%44,%45,%46,%47"
#define ACC_REGS "{" ACC48_REGS ",%48,%49,%50,%51}"
#define ACC48_OPS(c, d)                                                                                      \
  c(d[0]), c(d[1]), c(d[2]), c(d[3]), c(d[4]), c(d[5]), c(d[6]), c(d[7]), c(d[8]), c(d[9]), c(d[10]),        \
  c(d[11]), c(d[12]), c(d[13]), c(d[14]), c(d[15]), c(d[16]), c(d[17]), c(d[18]), c(d[19]), c(d[20]),        \
  c(d[21]), c(d[22]), c(d[23]), c(d[24]), c(d[25]), c(d[26]), c(d[27]), c(d[28]), c(d[29]), c(d[30]),        \
  c(d[31]), c(d[32]), c(d[33]), c(d[34]), c(d[35]), c(d[36]), c(d[37]), c(d[38]), c(d[39]), c(d[40]),        \
  c(d[41]), c(d[42]), c(d[43]), c(d[44]), c(d[45]), c(d[46]), c(d[47])
#define ACC_OPS(c, d) ACC48_OPS(c, d), c(d[48]), c(d[49]), c(d[50]), c(d[51])

template <int N = 104>
__device__ __forceinline__ void fence_acc(float (&d)[52]) {
  if constexpr (N == 104) asm volatile("" : ACC_OPS("+f", d)::"memory");
  else asm volatile("" : ACC48_OPS("+f", d)::"memory");
}

template <int N, int ACC>
__device__ __forceinline__ void mma_rs(float (&d)[52], uint32_t a0, uint32_t a1, uint32_t a2, uint32_t a3, uint64_t db) {
  if constexpr (N == 104 && ACC) {
    asm volatile("wgmma.mma_async.sync.aligned.m64n104k16.f32.bf16.bf16 " ACC_REGS
                 ", {%52,%53,%54,%55}, %56, %57, 1, 1, 0;\n"
                 : ACC_OPS("+f", d)
                 : "r"(a0), "r"(a1), "r"(a2), "r"(a3), "l"(db), "n"(ACC & 1));
  } else if constexpr (N == 104) {
    asm volatile("wgmma.mma_async.sync.aligned.m64n104k16.f32.bf16.bf16 " ACC_REGS
                 ", {%52,%53,%54,%55}, %56, 0, 1, 1, 0;\n"
                 : ACC_OPS("=f", d)
                 : "r"(a0), "r"(a1), "r"(a2), "r"(a3), "l"(db));
  } else if constexpr (ACC) {
    asm volatile("wgmma.mma_async.sync.aligned.m64n96k16.f32.bf16.bf16 {" ACC48_REGS
                 "}, {%48,%49,%50,%51}, %52, %53, 1, 1, 0;\n"
                 : ACC48_OPS("+f", d)
                 : "r"(a0), "r"(a1), "r"(a2), "r"(a3), "l"(db), "n"(ACC & 1));
  } else {
    asm volatile("wgmma.mma_async.sync.aligned.m64n96k16.f32.bf16.bf16 {" ACC48_REGS
                 "}, {%48,%49,%50,%51}, %52, 0, 1, 1, 0;\n"
                 : ACC48_OPS("=f", d)
                 : "r"(a0), "r"(a1), "r"(a2), "r"(a3), "l"(db));
  }
}
template <bool ACC>
__device__ __forceinline__ void mma_ss(float (&d)[52], uint64_t da, uint64_t db) {
  if constexpr (ACC) {
    asm volatile("wgmma.mma_async.sync.aligned.m64n104k16.f32.bf16.bf16 " ACC_REGS ", %52, %53, 1, 1, 1, 0, 0;\n"
                 : ACC_OPS("+f", d)
                 : "l"(da), "l"(db));
  } else {
    asm volatile("wgmma.mma_async.sync.aligned.m64n104k16.f32.bf16.bf16 " ACC_REGS ", %52, %53, 0, 1, 1, 0, 0;\n"
                 : ACC_OPS("=f", d)
                 : "l"(da), "l"(db));
  }
}

__device__ __forceinline__ uint64_t desc_sw128(uint32_t saddr) {
  return (uint64_t)((saddr & 0x3FFFF) >> 4) | ((uint64_t)1 << 16) | ((uint64_t)(1024 >> 4) << 32) | ((uint64_t)1 << 62);
}
__device__ __forceinline__ uint64_t desc_p(uint32_t saddr) {
  return (uint64_t)((saddr & 0x3FFFF) >> 4) | ((uint64_t)(128 >> 4) << 16) | ((uint64_t)(kPGrp >> 4) << 32);
}

__device__ __forceinline__ uint32_t pack_bf16(float lo, float hi) {
  uint32_t r;
  asm("cvt.rn.bf16x2.f32 %0, %1, %2;\n" : "=r"(r) : "f"(hi), "f"(lo));
  return r;
}
__device__ __forceinline__ uint32_t pack_bf16_relu(float lo, float hi) {
  uint32_t r;
  asm("cvt.rn.relu.bf16x2.f32 %0, %1, %2;\n" : "=r"(r) : "f"(hi), "f"(lo));
  return r;
}
__device__ __forceinline__ float ex2(float x) {
  float y;
  asm("ex2.approx.ftz.f32 %0, %1;\n" : "=f"(y) : "f"(x));
  return y;
}
__device__ __forceinline__ float rcp(float x) {
  float y;
  asm("rcp.approx.ftz.f32 %0, %1;\n" : "=f"(y) : "f"(x));
  return y;
}
__device__ __forceinline__ void stsm_x4(uint32_t addr, uint32_t r0, uint32_t r1, uint32_t r2, uint32_t r3) {
  asm volatile("stmatrix.sync.aligned.m8n8.x4.shared.b16 [%0], {%1,%2,%3,%4};\n" ::"r"(addr), "r"(r0), "r"(r1), "r"(r2), "r"(r3) : "memory");
}
__device__ __forceinline__ void stsm_x1(uint32_t addr, uint32_t r0) {
  asm volatile("stmatrix.sync.aligned.m8n8.x1.shared.b16 [%0], {%1};\n" ::"r"(addr), "r"(r0) : "memory");
}
__device__ __forceinline__ void stsm_x4_t(uint32_t addr, uint32_t r0, uint32_t r1, uint32_t r2, uint32_t r3) {
  asm volatile("stmatrix.sync.aligned.m8n8.x4.trans.shared.b16 [%0], {%1,%2,%3,%4};\n" ::"r"(addr), "r"(r0), "r"(r1), "r"(r2), "r"(r3) : "memory");
}
__device__ __forceinline__ void stsm_x2_t(uint32_t addr, uint32_t r0, uint32_t r1) {
  asm volatile("stmatrix.sync.aligned.m8n8.x2.trans.shared.b16 [%0], {%1,%2};\n" ::"r"(addr), "r"(r0), "r"(r1) : "memory");
}
__device__ __forceinline__ void ldsm_x4_t(uint32_t addr, uint32_t& r0, uint32_t& r1, uint32_t& r2, uint32_t& r3) {
  asm volatile("ldmatrix.sync.aligned.m8n8.x4.trans.shared.b16 {%0,%1,%2,%3}, [%4];\n" : "=r"(r0), "=r"(r1), "=r"(r2), "=r"(r3) : "r"(addr) : "memory");
}
__device__ __forceinline__ int lds(uint32_t addr) {
  int v;
  asm volatile("ld.shared.u32 %0, [%1];\n" : "=r"(v) : "r"(addr) : "memory");
  return v;
}
__device__ __forceinline__ void mbar_init(uint32_t bar, int count) {
  asm volatile("mbarrier.init.shared::cta.b64 [%0], %1;\n" ::"r"(bar), "r"(count) : "memory");
}
__device__ __forceinline__ void mbar_expect_tx(uint32_t bar, int bytes) {
  asm volatile("mbarrier.arrive.expect_tx.shared::cta.b64 _, [%0], %1;\n" ::"r"(bar), "r"(bytes) : "memory");
}
__device__ __forceinline__ void mbar_wait(uint32_t bar, uint32_t parity) {
  asm volatile(
      "{\n.reg .pred p;\n"
      "WAIT_%=:\n"
      "mbarrier.try_wait.parity.shared::cta.b64 p, [%0], %1;\n"
      "@p bra DONE_%=;\n"
      "bra WAIT_%=;\n"
      "DONE_%=:\n}\n" ::"r"(bar), "r"(parity) : "memory");
}
__device__ __forceinline__ void tma_load_2d(uint32_t dst, const CUtensorMap* tm, int c0, int c1, uint32_t bar) {
  asm volatile("cp.async.bulk.tensor.2d.shared::cluster.global.mbarrier::complete_tx::bytes [%0], [%1, {%3, %4}], [%2];\n" ::"r"(dst),
               "l"(tm), "r"(bar), "r"(c0), "r"(c1) : "memory");
}
__device__ __forceinline__ void tma_store_2d(const CUtensorMap* tm, uint32_t src, int c0, int c1) {
  asm volatile("cp.async.bulk.tensor.2d.global.shared::cta.bulk_group [%0, {%2, %3}], [%1];\n" ::"l"(tm), "r"(src), "r"(c0), "r"(c1) : "memory");
}

template <int N, int FIRST, int S0 = 0, int S1 = 8>
__device__ __forceinline__ void proj(float (&acc)[52], const uint32_t (&w)[32], uint64_t de) {
  wg_fence();
#pragma unroll
  for (int s = S0; s < S1; s++) {
    uint64_t db = de + (uint64_t)(((s >> 2) * kEHalf + (s & 3) * 32) >> 4);
    if (s == 0) mma_rs<N, FIRST>(acc, w[0], w[1], w[2], w[3], db);
    else mma_rs<N, 1>(acc, w[4 * s], w[4 * s + 1], w[4 * s + 2], w[4 * s + 3], db);
  }
  wg_commit();
}
__device__ __forceinline__ void issue_pv(float (&a)[52], const uint32_t (&vf)[28], uint64_t dp) {
  wg_fence();
#pragma unroll
  for (int s = 0; s < 6; s++) mma_rs<104, 1>(a, vf[4 * s], vf[4 * s + 1], vf[4 * s + 2], vf[4 * s + 3], dp + 16 * s);
  mma_rs<104, 1>(a, vf[24], vf[25], vf[26], vf[27], (dp + 16 * 6) & ~((uint64_t)0x3FFF << 16));
  wg_commit();
}
__device__ __forceinline__ void issue_s(float (&acc)[52], uint64_t dq, uint64_t dk) {
  wg_fence();
#pragma unroll
  for (int s = 0; s < 4; s++) {
    if (s == 0) mma_ss<false>(acc, dq, dk);
    else mma_ss<true>(acc, dq + 2 * s, dk + 2 * s);
  }
  wg_commit();
}

__device__ __forceinline__ void sched_barrier() { asm volatile("pmevent 1;\n" ::: "memory"); }
#define PIN(x) asm volatile("" : "+f"(x)::"memory")

constexpr float kC = 0.125f * 1.4426950408889634f;

__device__ __forceinline__ bool out_of_range(float t) { return !(t >= 0x1p-30f && t <= 0x1p30f); }
__device__ __forceinline__ uint32_t mul_bf16x2(uint32_t a, uint32_t b) {
  uint32_t r;
  asm("mul.rn.bf16x2 %0, %1, %2;\n" : "=r"(r) : "r"(a), "r"(b));
  return r;
}
__device__ __forceinline__ float quad_sum(float t) {
  t += __shfl_xor_sync(0xffffffffu, t, 1);
  t += __shfl_xor_sync(0xffffffffu, t, 2);
  return t;
}
struct Q3 { float t, s1, s2, s3; };
__device__ __forceinline__ Q3 q3_start(float t) {
  Q3 q;
  q.t = t;
  q.s1 = __shfl_xor_sync(0xffffffffu, t, 1);
  q.s2 = __shfl_xor_sync(0xffffffffu, t, 2);
  q.s3 = __shfl_xor_sync(0xffffffffu, t, 3);
  return q;
}
__device__ __forceinline__ float q3_end(const Q3& q) { return (q.t + q.s1) + (q.s2 + q.s3); }
template <int O, int J0, int J1>
__device__ __forceinline__ void part_exp(const float (&s)[52], uint32_t (&p)[13], bool tail_invalid, float& t0, float& t1) {
#pragma unroll
  for (int j = J0; j < J1; j++) {
    const int jj = (j + 12) % 13;
    float x = ex2(s[4 * jj + O]), y = ex2(s[4 * jj + O + 1]);
    if (jj == 12 && tail_invalid) { x = 0.f; y = 0.f; }
    p[jj] = pack_bf16(x, y);
    if (j == 0) { t0 = x; t1 = y; } else { t0 += x; t0 += y; }
  }
}
template <int O>
__device__ __forceinline__ float set_max(const float (&s)[52], bool tail_invalid) {
  float m = fmaxf(s[O], s[O + 1]);
#pragma unroll
  for (int j = 1; j < 12; j++) m = fmaxf(m, fmaxf(s[4 * j + O], s[4 * j + O + 1]));
  if (!tail_invalid) m = fmaxf(m, fmaxf(s[48 + O], s[49 + O]));
  m = fmaxf(m, __shfl_xor_sync(0xffffffffu, m, 1));
  return fmaxf(m, __shfl_xor_sync(0xffffffffu, m, 2));
}
template <int O>
__device__ __forceinline__ float set_exact(const float (&s)[52], uint32_t (&p)[13], bool tail_invalid, float m) {
  float t0, t1;
#pragma unroll
  for (int j = 0; j < 13; j++) {
    const int jj = (j + 12) % 13;
    float x = ex2(s[4 * jj + O] - m), y = ex2(s[4 * jj + O + 1] - m);
    if (jj == 12 && tail_invalid) { x = 0.f; y = 0.f; }
    p[jj] = pack_bf16(x, y);
    if (j == 0) { t0 = x; t1 = y; } else { t0 += x; t1 += y; }
  }
  return quad_sum(t0 + t1);
}
__device__ __forceinline__ uint32_t inv2(float t) { const float iv = rcp(t); return pack_bf16(iv, iv); }
template <int C>
__device__ __forceinline__ void part_store(const uint32_t (&p)[13], uint32_t iv, uint32_t paddr) {
  if (C < 3) stsm_x4(paddr + C * 512, mul_bf16x2(p[4 * C], iv), mul_bf16x2(p[4 * C + 1], iv), mul_bf16x2(p[4 * C + 2], iv), mul_bf16x2(p[4 * C + 3], iv));
  else stsm_x1(paddr + 1536, mul_bf16x2(p[12], iv));
}
__device__ __forceinline__ void set_store(const uint32_t (&p)[13], float t, uint32_t paddr) {
  const uint32_t iv = inv2(t);
  part_store<0>(p, iv, paddr);
  part_store<1>(p, iv, paddr);
  part_store<2>(p, iv, paddr);
  part_store<3>(p, iv, paddr);
}

struct Params {
  const uint8_t* w[4];
  uint8_t* out;
  unsigned* claim;
  short n_pairs, n_extra, n_open, streams;
};
struct Maps { CUtensorMap m[7]; };
using I104 = std::integral_constant<int, 104>;
using I96 = std::integral_constant<int, 96>;

__global__ void __launch_bounds__(512, 1)
autoint_kernel(const __grid_constant__ Params prm, const __grid_constant__ Maps tm) {
  extern __shared__ __align__(1024) uint8_t smem[];
  const uint32_t sbase = smem_u32(smem);
  const int tid = threadIdx.x;
  const uint32_t bar_full = sbase + kBarOff;
  const uint32_t bar_w = sbase + kBarOff + 64;
  const int cta = blockIdx.x, stream = cta >> 1, head = cta & 1;
  if (tid >= 256 && tid < 448) {
    if ((tid & 31) == 0) {
      const int k = (tid >> 5) - 8, m = (0x402153 >> (4 * (5 - k))) & 15;
      const uint32_t bar = m == 5 ? bar_full : bar_w + 8 * m;
      const uint32_t dst = sbase + (m == 0 ? kPOff : m == 1 ? kWkOff : m < 4 ? (m + 1) * kEStage : (m - 4) * kEHalf);
      const int c0 = m == 3 ? head * 64 : m == 5 ? 64 : 0, c1 = m < 3 ? head * 128 : m == 3 ? 0 : stream * 2 * kF;
      mbar_init(bar, 1);
      asm volatile("fence.mbarrier_init.release.cluster;\n" ::: "memory");
      fence_async();
      const long long c = clock64();
      while (clock64() - c < k * 60) {}
      mbar_expect_tx(bar, m < 4 ? 16384 : kEHalf);
      tma_load_2d(dst, &tm.m[m < 4 ? m + 2 : 0], c0, c1, bar);
    }
  } else if (tid == 448) {
    for (int s = 1; s < kStages; s++) mbar_init(bar_full + 8 * s, 1);
    asm volatile("fence.mbarrier_init.release.cluster;\n" ::: "memory");
    asm volatile("st.shared.v2.u32 [%0], {%1,%1};\n" ::"r"(sbase + kZeroOff), "r"(0) : "memory");
    fence_async();
  } else if (tid < 192) {
    if (tid == 0 || tid == 160) asm volatile("prefetch.tensormap [%0];\n" ::"l"(&tm.m[1 + (tid >> 5)]) : "memory");
  } else if (tid >= 224) {
    if (tid < 250) asm volatile("st.shared.v4.u32 [%0], {%1,%1,%1,%1};\nst.shared.v4.u32 [%0 + 16], {%1,%1,%1,%1};\n"
                                ::"r"(sbase + kPOff + 12 * kPGrp + ((tid - 224) >> 1) * 128 + 64 + (tid & 1) * 32), "r"(0) : "memory");
  } else if (tid < 200) {
    asm volatile("prefetch.global.L2 [%0];\n" ::"l"(prm.w[(cta >> 5) & 3] + (cta & 31) * 1024 + (tid & 7) * 128) : "memory");
  }
  const int wg = __shfl_sync(0xffffffffu, tid >> 7, 0);
  __syncthreads();
  sched_barrier();
  const int n_pairs = prm.n_pairs, n_open = prm.n_open, streams = prm.streams;
  const int n_static = 2 * (n_pairs + (stream < prm.n_extra));
  const int n_tiles = n_static + (n_open > 0);
  auto row_of = [&](int i) {
    return i < n_static ? (((i >> 1) * streams + stream) * 2 + (i & 1)) * kF : lds(sbase + kCntOff + 4);
  };
  auto load_e = [&](int i) {
    const uint32_t dst = sbase + (i % kStages) * kEStage, bar = bar_full + 8 * (i % kStages);
    const int row = row_of(i) + (i & 1) * 4;
    mbar_expect_tx(bar, (i & 1) ? 2 * 96 * 128 : 2 * 104 * 128);
    tma_load_2d(dst, &tm.m[i & 1], 0, row, bar);
    tma_load_2d(dst + kEHalf, &tm.m[i & 1], 64, row, bar);
  };
  auto wait_e = [&](int i) { mbar_wait(bar_full + 8 * (i % kStages), (i / kStages) & 1); };
  auto read_count = [&]() { return __shfl_sync(0xffffffffu, lds(sbase + kCntOff), 0); };

#define ROLE_IDS()                                                                                     \
  int rtid;                                                                                            \
  asm volatile("mov.u32 %0, %tid.x;\n" : "=r"(rtid));                                                  \
  const int lane = rtid & 31;                                                                          \
  [[maybe_unused]] const int warp = __shfl_sync(0xffffffffu, (rtid >> 5) & 3, 0);                      \
  [[maybe_unused]] const uint32_t chunk = ((rtid >> 4) & 6) + ((lane >> 3) & 1);                       \
  [[maybe_unused]] const uint32_t t_off = ((lane >> 4) * 8 + (lane & 7)) * 128 + ((chunk ^ (lane & 7)) << 4)
  auto load_frags = [&](uint32_t (&w)[32], int m, uint32_t addr) {
    mbar_wait(bar_w + 8 * m, 0);
#pragma unroll
    for (int s = 0; s < 8; s++) ldsm_x4_t(addr + s * 2048, w[4 * s], w[4 * s + 1], w[4 * s + 2], w[4 * s + 3]);
  };
  const uint64_t dE0 = desc_sw128(sbase);
  auto finish = [&](int rtid, int n_items) {
    uint8_t* dst = prm.out + (size_t)row_of(n_items - 1) * (kD * 2) + head * 128;
    bar_sync(BAR_W, 512);
#pragma unroll
    for (int k = 0; k < 2; k++) {
      const int c = rtid + 512 * k, r = c >> 3;
      if (c < 8 * kF) {
        uint4 v;
        asm volatile("ld.shared.v4.u32 {%0,%1,%2,%3}, [%4];\n" : "=r"(v.x), "=r"(v.y), "=r"(v.z), "=r"(v.w)
                     : "r"(sbase + kOOff + r * 128 + (((c ^ r) & 7) << 4)) : "memory");
        *(uint4*)(dst + r * (kD * 2) + (c & 7) * 16) = v;
      }
    }
  };

  if (wg == 0) {
    asm volatile("setmaxnreg.inc.sync.aligned.u32 144;\n");
    ROLE_IDS();
    uint32_t wQ[32], wK[32];
    float acc[52];
    load_frags(wQ, 0, sbase + kPOff + t_off);
#pragma unroll
    for (int i = 0; i < 32; i++) wQ[i] = pack_bf16(__uint_as_float(wQ[i] << 16) * kC, __uint_as_float(wQ[i] & 0xffff0000u) * kC);
    int n_items = n_static;
    const uint32_t k_addr = sbase + kKOff + t_off, q_addr = sbase + kQOff + t_off, q_hi = q_addr + (lane & 16) * 64;
    uint32_t pk[26];
    auto pack = [&](auto NC) {
      constexpr int N = decltype(NC)::value;
      wg_wait<0>();
      fence_acc<N>(acc);
#pragma unroll
      for (int i = 0; i < N / 4; i++) pk[i] = pack_bf16(acc[2 * i], acc[2 * i + 1]);
    };
    auto publish = [&](int it) {
      const int n = it >= 2 ? 384 : 256;
      fence_async();
      bar_arrive(BAR_X, n);
      bar_arrive(BAR_X + 1, n);
    };
    auto item = [&](auto NC, auto FC, int it) {
      constexpr int N = decltype(NC)::value;
      constexpr bool first = decltype(FC)::value;
      constexpr int kPre = first ? 4 : 8;
      const uint64_t dE = dE0 + (uint64_t)(((it % kStages) * kEStage) >> 4);
      auto store_q = [&](int j0, int j1) {
#pragma unroll
        for (int j = j0; j < j1; j += 2) {
          if (j < 8) stsm_x4_t(q_addr + j * 1024, pk[2 * j], pk[2 * j + 1], pk[2 * j + 2], pk[2 * j + 3]);
          else if (j < 12) stsm_x4_t(q_hi + (2 * j - 8) * 1024, pk[2 * j], pk[2 * j + 1], pk[2 * j + 2], pk[2 * j + 3]);
          else if (N == 104) {
            stsm_x4_t(q_hi + 9 * 1024, pk[24], pk[25], pk[24], pk[25]);
            stsm_x4_t(q_hi + 13 * 1024, pk[24], pk[25], pk[24], pk[25]);
          }
        }
      };
      if (first) {
        mbar_wait(bar_w + 32, 0);
        proj<N, 0, 0, 4>(acc, wQ, dE);
        bar_arrive(BAR_T1, 256);
        load_frags(wK, 1, q_addr + (kWkOff - kQOff));
        mbar_wait(bar_full, 0);
        proj<N, 0, 4, 8>(acc, wQ, dE);
        bar_arrive(BAR_S1, 256);
      } else {
        if (it >= 3) bar_sync(BAR_T1, 256);
        proj<N, 0>(acc, wQ, dE);
        if (N == 104 || it > 1) publish(it - 1);
        else bar_arrive(BAR_X + 1, 256);
      }
      pack(NC);
#pragma unroll
      for (int i = 0; i < N / 4; i++) asm volatile("" : "+r"(pk[i])::"memory");
      sched_barrier();
      if (!first) bar_sync(BAR_QE, 256);
      store_q(0, kPre);
      if (!first) bar_sync(BAR_SP + 1, 256);
      proj<N, 2>(acc, wK, dE);
      if (N == 104 && !first && it == 2) bar_arrive(BAR_S2, 256);
      if (first) bar_arrive(BAR_O, 256);
      store_q(kPre, 8);
      if (!first) {
        if (it + 1 < n_tiles) wait_e(it + 1);
        bar_sync(BAR_QE + 1, 256);
      }
      store_q(8, 14);
      if (N == 96 && it + 1 == n_static) n_items = read_count();
      pack(NC);
#pragma unroll
      for (int j = 0; j < 12; j += 2) stsm_x4_t(k_addr + j * 1024, pk[2 * j], pk[2 * j + 1], pk[2 * j + 2], pk[2 * j + 3]);
      if (N == 104) stsm_x2_t(k_addr + 12 * 1024, pk[24], pk[25]);
      if (first) {
        fence_async();
        bar_arrive(BAR_X, 256);
        wait_e(1);
        bar_sync(BAR_SP, 256);
      }
    };
    item(I104{}, std::true_type{}, 0);
    for (int it = 1;; it += 2) {
      item(I96{}, std::false_type{}, it);
      if (it + 1 == n_items) break;
      item(I104{}, std::false_type{}, it + 1);
      if (it + 2 == n_items) break;
    }
    publish(n_items - 1);
    finish(rtid, n_items);
  } else if (wg == 1) {
    asm volatile("setmaxnreg.inc.sync.aligned.u32 176;\n");
    ROLE_IDS();
    uint32_t wV[32], wR[32];
    float acc[52];
    uint32_t vf[28], pl[2];
    asm volatile("ld.volatile.shared.v2.u32 {%0, %1}, [%2];\n" : "=r"(vf[26]), "=r"(vf[27]) : "r"(sbase + kZeroOff) : "memory");
    load_frags(wV, 2, sbase + 3 * kEStage + t_off);
    int n_items = n_static;
    const uint32_t o_even = sbase + kOOff + t_off;
    const uint32_t r4 = (lane & 7) + 4;
    const uint32_t o_odd = sbase + kOOff + ((lane >> 4) * 8 + r4) * 128 + ((chunk ^ (r4 & 7)) << 4);
    const uint32_t o_odd_last = sbase + kOOff + ((lane & 4) ? (r4 & 7) : 96 + r4) * 128 + ((chunk ^ (r4 & 7)) << 4);
    const uint64_t dP = desc_p(sbase + kPOff);
    auto store_o = [&](int par, int it) {
      const uint32_t a = par ? o_odd : o_even;
      if (it >= 1) bar_sync(BAR_OF, 160);
#pragma unroll
      for (int j = 0; j < 12; j += 2) stsm_x4_t(a + j * 1024, vf[2 * j], vf[2 * j + 1], vf[2 * j + 2], vf[2 * j + 3]);
      stsm_x2_t(par ? o_odd_last : o_even + 12 * 1024, pl[0], pl[1]);
    };
    auto item = [&](auto NC, auto FC, int it) {
      constexpr int N = decltype(NC)::value, par = N == 96;
      constexpr bool first = decltype(FC)::value;
      const uint64_t dE = dE0 + (uint64_t)(((it % kStages) * kEStage) >> 4);
      if (first) {
        mbar_wait(bar_w + 32, 0);
        bar_sync(BAR_T1, 256);
        proj<N, 0, 0, 4>(acc, wV, dE);
        mbar_wait(bar_full, 0);
        bar_sync(BAR_S1, 256);
        proj<N, 0, 4, 8>(acc, wV, dE);
        load_frags(wR, 3, o_even + (4 * kEStage - kOOff));
        bar_arrive(BAR_W, 160);
      } else {
#pragma unroll
        for (int i = 0; i < 24; i++) asm volatile("" : "+r"(vf[i])::"memory");
        asm volatile("" : "+r"(pl[0]), "+r"(pl[1])::"memory");
        sched_barrier();
        if (it + 1 < n_items) bar_sync(BAR_SP, 256);
        proj<N, 2>(acc, wV, dE);
        if (it + 1 < n_items) bar_arrive(BAR_X + 1, 384);
        bar_sync(BAR_PF + par, 384);
        fence_async();
        if (par && it + 3 == n_static) n_items = read_count();
        store_o(par ^ 1, it - 1);
        bar_arrive(BAR_O, 160);
      }
      wg_wait<0>();
      fence_acc<N>(acc);
#pragma unroll
      for (int i = 0; i < N / 4; i++) {
        if (!first) asm("cvt.rn.bf16x2.f32 %0, %1, %2;\n" : "+r"(vf[i]) : "f"(acc[2 * i + 1]), "f"(acc[2 * i]));
        else vf[i] = pack_bf16(acc[2 * i], acc[2 * i + 1]);
      }
      if (first) bar_sync(BAR_O, 256);
      proj<N, 2>(acc, wR, dE);
      if (first) {
        bar_sync(BAR_PF + par, 384);
        fence_async();
        bar_sync(BAR_SP, 256);
        bar_sync(BAR_S2, 256);
      }
      issue_pv(acc, vf, dP + (uint64_t)((par * kPBuf) >> 4));
      if (it + 3 < n_items) bar_arrive(BAR_T1, 256);
      if (it + 1 < n_items) wait_e(it + 1);
      wg_wait<0>();
      if (it + 2 < n_items) bar_arrive(BAR_X, 384);
      sched_barrier();
      fence_acc(acc);
#pragma unroll
      for (int i = 0; i < 24; i++) asm("cvt.rn.relu.bf16x2.f32 %0, %1, %2;\n" : "+r"(vf[i]) : "f"(acc[2 * i + 1]), "f"(acc[2 * i]));
      pl[0] = pack_bf16_relu(acc[48], acc[49]);
      pl[1] = pack_bf16_relu(acc[50], acc[51]);
    };
    item(I104{}, std::true_type{}, 0);
    for (int it = 1;; it += 2) {
      item(I96{}, std::false_type{}, it);
      if (it + 1 == n_items) break;
      item(I104{}, std::false_type{}, it + 1);
      if (it + 2 == n_items) break;
    }
    store_o((n_items - 1) & 1, n_items - 1);
    finish(rtid, n_items);
  } else {
    asm volatile("setmaxnreg.dec.sync.aligned.u32 96;\n");
    ROLE_IDS();
    const uint64_t dK = desc_sw128(sbase + kKOff);
    float acc[52];
    if (wg == 2) {
      const uint64_t dQ = desc_sw128(sbase + kQOff);
      uint32_t pa = sbase + kPOff + 2 * warp * kPGrp + lane * 16;
      int tail = (lane >> 1) & 1;
      if (rtid == 256) {
        mbar_wait(bar_w + 32, 0);
        load_e(1);
        mbar_wait(bar_full, 0);
        load_e(2);
      }
      if (rtid == 320) {
        const int m = max(n_open, 1), x = stream % m;
        asm volatile("st.shared.v4.u32 [%0], {%1,%2,%3,%4};\n" ::"r"(sbase + kCntOff), "r"(n_static), "r"((2 * n_pairs * streams + x) * kF),
                     "r"(2 * x + head), "r"((streams - 1 - x) / m) : "memory");
      }
      if (warp == kServe) bar_sync(BAR_W, 160);
      __syncwarp();
      int n_items = n_static;
      for (int it = 0; it < n_items; it++) {
        bar_sync(BAR_X, it >= 2 ? 384 : 256);
        issue_s(acc, dQ, dK);
        bar_arrive(BAR_SP, 256);
        if (warp == kServe && lane == 0 && it + 3 < n_tiles) load_e(it + 3);
        if (it + 1 == n_static) n_items = read_count();
        wg_wait<0>();
        if (it + 1 < n_items) bar_arrive(BAR_QE, 256);
        sched_barrier();
        fence_acc(acc);
        uint32_t p0[13], p1[13];
        float t0, t1, u0, u1;
        part_exp<0, 0, 13>(acc, p0, tail, t0, u0);
        part_exp<2, 0, 2>(acc, p1, tail, t1, u1);
        t0 += u0;
        u0 = __shfl_xor_sync(0xffffffffu, t0, 1);
        PIN(t1); PIN(u1);
        sched_barrier();
        part_exp<2, 2, 6>(acc, p1, tail, t1, u1);
        PIN(t1); PIN(u1);
        sched_barrier();
        t0 += u0;
        u0 = __shfl_xor_sync(0xffffffffu, t0, 2);
        sched_barrier();
        part_exp<2, 6, 10>(acc, p1, tail, t1, u1);
        PIN(t1); PIN(u1);
        sched_barrier();
        t0 += u0;
        const uint32_t i0 = inv2(t0);
        part_exp<2, 10, 13>(acc, p1, tail, t1, u1);
        part_store<0>(p0, i0, pa);
        const Q3 q1 = q3_start(t1 + u1);
        sched_barrier();
        part_store<1>(p0, i0, pa);
        part_store<2>(p0, i0, pa);
        part_store<3>(p0, i0, pa);
        sched_barrier();
        t1 = q3_end(q1);
        if (__builtin_expect(__any_sync(0xffffffffu, out_of_range(t0) || out_of_range(t1)), 0)) {
          set_store(p0, set_exact<0>(acc, p0, tail, set_max<0>(acc, tail)), pa);
          t1 = set_exact<2>(acc, p1, tail, set_max<2>(acc, tail));
        }
        set_store(p1, t1, pa + kPGrp);
        bar_arrive(BAR_PF + (it & 1), 384);
        pa += (it & 1) ? -kPBuf : kPBuf;
        tail ^= 1;
      }
      finish(rtid, n_items);
    } else {
      const uint64_t dQ = desc_sw128(sbase + kQOff + 8192);
      const bool server = warp == kServe;
      auto serve = [&](int it) {
        bar_sync(BAR_O, 160);
        if (lane == 0) {
          fence_async();
          tma_store_2d(&tm.m[6], sbase + kOOff, head * 64, row_of(it));
          asm volatile("cp.async.bulk.commit_group;\n" ::: "memory");
        }
        __syncwarp();
      };
      auto release_o = [&]() {
        if (lane == 0) asm volatile("cp.async.bulk.wait_group.read 0;\n" ::: "memory");
        __syncwarp();
        bar_arrive(BAR_OF, 160);
      };
      uint32_t pa = sbase + kPOff + (8 + warp) * kPGrp + lane * 16;
      const uint32_t trash = sbase + kTrashOff + lane * 16;
      const uint32_t pd = sbase + kPOff + 12 * kPGrp + (3 * warp + (lane >> 3)) * 128 + (lane & 7) * 16 + ((lane >> 2) & 1) * kPBuf;
      const bool exists = lane < 24 || warp == 3;
      uint32_t pd0 = exists && !(lane & 4) ? pd : trash, pd1 = exists && (lane & 4) ? pd : trash;
      const uint32_t sum_addr = sbase + kSumOff + (lane >> 2) * 16;
      int tail = (lane >> 1) & 1, other = lane >> 4;
      int n_items = n_static;
      uint32_t ticket = 1;
      for (int it = 0; it < n_items; it++) {
        bar_sync(BAR_X + 1, it >= 2 ? 384 : 256);
        issue_s(acc, dQ, dK);
        if (it + 1 < n_items) bar_arrive(BAR_SP + 1, 256);
        if (it + 2 == n_static) n_items = read_count();
        wg_wait<0>();
        if (it + 1 < n_items) bar_arrive(BAR_QE + 1, 256);
        if (server && it >= 2) serve(it - 2);
        if (ticket == 0) asm volatile("st.shared.u32 [%0], %1;\n" ::"r"(sbase + kCntOff), "r"(n_static + 1) : "memory");
        sched_barrier();
        fence_acc(acc);
        uint32_t p0[13], d[4];
        float td;
        auto d_exp = [&](auto WC, auto SC, float m) {
          constexpr int W = decltype(WC)::value;
          constexpr bool SUB = decltype(SC)::value;
          float x[8];
#pragma unroll
          for (int k = 0; k < (W == 3 ? 8 : 6); k++) {
            const float v = acc[4 * (3 * W + (k >> 1)) + 2 + (k & 1)];
            x[k] = ex2(SUB ? v - m : v);
          }
          td = ((x[0] + x[1]) + (x[2] + x[3])) + (x[4] + x[5]);
          if (W == 3) {
            if (tail) { x[6] = 0.f; x[7] = 0.f; }
            td += x[6] + x[7];
            d[3] = pack_bf16(x[6], x[7]);
          } else d[3] = 0;
#pragma unroll
          for (int k = 0; k < 3; k++) d[k] = pack_bf16(x[2 * k], x[2 * k + 1]);
        };
        auto d_exp_w = [&](auto SC, float m) {
          if (warp == 0) d_exp(std::integral_constant<int, 0>{}, SC, m);
          else if (warp == 1) d_exp(std::integral_constant<int, 1>{}, SC, m);
          else if (warp == 2) d_exp(std::integral_constant<int, 2>{}, SC, m);
          else d_exp(std::integral_constant<int, 3>{}, SC, m);
        };
        d_exp_w(std::false_type{}, 0.f);
        float t0, u0, ud = __shfl_xor_sync(0xffffffffu, td, 1);
        sched_barrier();
        part_exp<0, 0, 4>(acc, p0, tail, t0, u0);
        PIN(t0); PIN(u0);
        sched_barrier();
        td += ud;
        ud = __shfl_xor_sync(0xffffffffu, td, 2);
        sched_barrier();
        part_exp<0, 4, 8>(acc, p0, tail, t0, u0);
        PIN(t0); PIN(u0);
        sched_barrier();
        asm volatile("st.shared.f32 [%0], %1;\n" ::"r"(sum_addr + warp * 4), "f"(td + ud) : "memory");
        sched_barrier();
        part_exp<0, 8, 13>(acc, p0, tail, t0, u0);
        const Q3 q0 = q3_start(t0 + u0);
        bar_sync(BAR_D, 128);
        float4 u;
        asm volatile("ld.shared.v4.f32 {%0,%1,%2,%3}, [%4];\n" : "=f"(u.x), "=f"(u.y), "=f"(u.z), "=f"(u.w) : "r"(sum_addr) : "memory");
        sched_barrier();
        t0 = q3_end(q0);
        set_store(p0, t0, pa);
        td = (u.x + u.y) + (u.z + u.w);
        if (__builtin_expect(__any_sync(0xffffffffu, out_of_range(t0) | (!other & out_of_range(td))), 0)) {
          set_store(p0, set_exact<0>(acc, p0, tail, set_max<0>(acc, tail)), pa);
          const float m = set_max<2>(acc, tail);
          d_exp_w(std::true_type{}, m);
          td = set_exact<2>(acc, p0, tail, m);
        }
        const uint32_t iv = inv2(td);
        stsm_x4(pd0, mul_bf16x2(d[0], iv), mul_bf16x2(d[1], iv), mul_bf16x2(d[2], iv), mul_bf16x2(d[3], iv));
        bar_arrive(BAR_PF + (it & 1), 384);
        if (server && it >= 2) release_o();
        ticket = 1;
        if (it + 4 == n_static && n_open > 0 && rtid == 384 + 32 * kClaim)
          asm volatile("atom.global.inc.u32 %0, [%1], %2;\n" : "=r"(ticket) : "l"(prm.claim + lds(sbase + kCntOff + 8)), "r"(lds(sbase + kCntOff + 12)) : "memory");
        pa += (it & 1) ? -kPBuf : kPBuf;
        tail ^= 1;
        other ^= 1;
        const uint32_t x = pd0; pd0 = pd1; pd1 = x;
      }
      if (server) {
        serve(n_items - 2);
        release_o();
      }
      finish(rtid, n_items);
    }
  }
}

typedef CUresult (*EncodeFn)(CUtensorMap*, CUtensorMapDataType, cuuint32_t, void*, const cuuint64_t*, const cuuint64_t*,
                             const cuuint32_t*, const cuuint32_t*, CUtensorMapInterleave, CUtensorMapSwizzle,
                             CUtensorMapL2promotion, CUtensorMapFloatOOBfill);

}

extern "C" void kernel_launch(void* const* d_in, const int* in_sizes, int n_in, void* d_out, int out_size) {
  static EncodeFn encode = nullptr;
  static int num_sms = 0;
  static unsigned* claim = nullptr;
  if (!encode) {
    void* fn = nullptr;
    cudaDriverEntryPointQueryResult qres;
    cudaGetDriverEntryPoint("cuTensorMapEncodeTiled", &fn, cudaEnableDefault, &qres);
    encode = (EncodeFn)fn;
    int dev = 0;
    cudaGetDevice(&dev);
    cudaDeviceGetAttribute(&num_sms, cudaDevAttrMultiProcessorCount, dev);
    cudaGetSymbolAddress((void**)&claim, g_claim);
    cudaFuncSetAttribute(autoint_kernel, cudaFuncAttributeMaxDynamicSharedMemorySize, kSmemBytes);
  }
  auto make = [&](void* p, uint64_t cols, uint64_t rows, uint32_t box_rows, CUtensorMapL2promotion promo) {
    CUtensorMap tm;
    cuuint64_t dims[2] = {cols, rows};
    cuuint64_t strides[1] = {cols * 2};
    cuuint32_t box[2] = {64, box_rows};
    cuuint32_t estr[2] = {1, 1};
    encode(&tm, CU_TENSOR_MAP_DATA_TYPE_BFLOAT16, 2, p, dims, strides, box, estr, CU_TENSOR_MAP_INTERLEAVE_NONE,
           CU_TENSOR_MAP_SWIZZLE_128B, promo, CU_TENSOR_MAP_FLOAT_OOB_FILL_NONE);
    return tm;
  };
  Maps tm;
  tm.m[0] = make(d_in[0], kD, (uint64_t)kB * kF, 104, CU_TENSOR_MAP_L2_PROMOTION_L2_128B);
  tm.m[1] = make(d_in[0], kD, (uint64_t)kB * kF, 96, CU_TENSOR_MAP_L2_PROMOTION_L2_256B);
  for (int i = 0; i < 3; i++) tm.m[2 + i] = make(d_in[1 + i], 64, 256, 128, CU_TENSOR_MAP_L2_PROMOTION_L2_256B);
  tm.m[5] = make(d_in[4], 128, 128, 128, CU_TENSOR_MAP_L2_PROMOTION_L2_256B);
  tm.m[6] = make(d_out, kD, (uint64_t)kB * kF, kF, CU_TENSOR_MAP_L2_PROMOTION_NONE);
  const int grid = (num_sms < 2 ? 2 : num_sms > 256 ? 256 : num_sms) & ~1, streams = grid / 2;
  const int n_pairs = kB / 2 / streams, rem = kB / 2 - n_pairs * streams;
  const bool open = 2 * rem <= streams;
  Params prm;
  for (int i = 0; i < 4; i++) prm.w[i] = (const uint8_t*)d_in[1 + i];
  prm.out = (uint8_t*)d_out;
  prm.claim = claim;
  prm.n_pairs = (short)n_pairs;
  prm.n_extra = (short)(open ? 0 : rem);
  prm.n_open = (short)(open ? 2 * rem : 0);
  prm.streams = (short)streams;
  autoint_kernel<<<grid, 512, kSmemBytes>>>(prm, tm);
}
```

```cpp
#include <cuda_runtime.h>
#include <cuda_bf16.h>
#include <cuda.h>
#include <stdint.h>
#include <type_traits>

namespace {

constexpr int kB = 4096, kF = 100, kD = 128;
constexpr int kStages = 5;
constexpr int kServe = 1, kClaim = 2;
constexpr int kEHalf = 104 * 128;
constexpr int kEStage = 2 * kEHalf;
constexpr int kQOff = kStages * kEStage;
constexpr int kKOff = kQOff + 16384;
constexpr int kPOff = kKOff + 13312;
constexpr int kPGrp = 13 * 128;
constexpr int kPBuf = 13 * kPGrp;
constexpr int kWkOff = kPOff + 22528;
constexpr int kOOff = kPOff + 44032;
constexpr int kBarOff = kOOff + 13312;
constexpr int kTrashOff = kBarOff + 128;
constexpr int kSumOff = kTrashOff + 512;
constexpr int kZeroOff = kSumOff + 128;
constexpr int kCntOff = kZeroOff + 16;
constexpr int kSmemBytes = kZeroOff + 128;
static_assert(kQOff % 1024 == 0 && kKOff % 1024 == 0 && kPOff % 1024 == 0 && kOOff % 1024 == 0 && kWkOff % 1024 == 0 &&
              2 * kPBuf <= 44032 && kWkOff >= kPOff + kPBuf && kWkOff + 16384 <= kOOff && kSmemBytes <= 232448, "smem layout");

enum {
  BAR_T1 = 1,
  BAR_X = 2,
  BAR_QE = 4,
  BAR_PF = 6,
  BAR_O = 8,
  BAR_S2 = 9,
  BAR_W = 10,
  BAR_SP = 11,
  BAR_OF = 13,
  BAR_D = 14,
  BAR_S1 = 15
};

__device__ unsigned g_claim[256];

__device__ __forceinline__ uint32_t smem_u32(const void* p) { return (uint32_t)__cvta_generic_to_shared(p); }

__device__ __forceinline__ void wg_fence() { asm volatile("wgmma.fence.sync.aligned;\n" ::: "memory"); }
__device__ __forceinline__ void wg_commit() { asm volatile("wgmma.commit_group.sync.aligned;\n" ::: "memory"); }
template <int N> __device__ __forceinline__ void wg_wait() { asm volatile("wgmma.wait_group.sync.aligned %0;\n" ::"n"(N) : "memory"); }
__device__ __forceinline__ void fence_async() { asm volatile("fence.proxy.async.shared::cta;\n" ::: "memory"); }
__device__ __forceinline__ void bar_sync(int id, int n) { asm volatile("bar.sync %0, %1;\n" ::"r"(id), "r"(n) : "memory"); }
__device__ __forceinline__ void bar_arrive(int id, int n) { asm volatile("bar.arrive %0, %1;\n" ::"r"(id), "r"(n) : "memory"); }

#define ACC48_REGS "%0,%1,%2,%3,%4,%5,%6,%7,%8,%9,%10,%11,%12,%13,%14,%15,%16,%17,%18,%19,%20,%21,%22,%23,%24,%25," \
                   "%26,%27,%28,%29,%30,%31,%32,%33,%34,%35,%36,%37,%38,%39,%40,%41,%42,%43,%44,%45,%46,%47"
#define ACC_REGS "{" ACC48_REGS ",%48,%49,%50,%51}"
#define ACC48_OPS(c, d)                                                                                      \
  c(d[0]), c(d[1]), c(d[2]), c(d[3]), c(d[4]), c(d[5]), c(d[6]), c(d[7]), c(d[8]), c(d[9]), c(d[10]),        \
  c(d[11]), c(d[12]), c(d[13]), c(d[14]), c(d[15]), c(d[16]), c(d[17]), c(d[18]), c(d[19]), c(d[20]),        \
  c(d[21]), c(d[22]), c(d[23]), c(d[24]), c(d[25]), c(d[26]), c(d[27]), c(d[28]), c(d[29]), c(d[30]),        \
  c(d[31]), c(d[32]), c(d[33]), c(d[34]), c(d[35]), c(d[36]), c(d[37]), c(d[38]), c(d[39]), c(d[40]),        \
  c(d[41]), c(d[42]), c(d[43]), c(d[44]), c(d[45]), c(d[46]), c(d[47])
#define ACC_OPS(c, d) ACC48_OPS(c, d), c(d[48]), c(d[49]), c(d[50]), c(d[51])

template <int N = 104>
__device__ __forceinline__ void fence_acc(float (&d)[52]) {
  if constexpr (N == 104) asm volatile("" : ACC_OPS("+f", d)::"memory");
  else asm volatile("" : ACC48_OPS("+f", d)::"memory");
}

template <int N, int ACC>
__device__ __forceinline__ void mma_rs(float (&d)[52], uint32_t a0, uint32_t a1, uint32_t a2, uint32_t a3, uint64_t db) {
  if constexpr (N == 104 && ACC) {
    asm volatile("wgmma.mma_async.sync.aligned.m64n104k16.f32.bf16.bf16 " ACC_REGS
                 ", {%52,%53,%54,%55}, %56, %57, 1, 1, 0;\n"
                 : ACC_OPS("+f", d)
                 : "r"(a0), "r"(a1), "r"(a2), "r"(a3), "l"(db), "n"(ACC & 1));
  } else if constexpr (N == 104) {
    asm volatile("wgmma.mma_async.sync.aligned.m64n104k16.f32.bf16.bf16 " ACC_REGS
                 ", {%52,%53,%54,%55}, %56, 0, 1, 1, 0;\n"
                 : ACC_OPS("=f", d)
                 : "r"(a0), "r"(a1), "r"(a2), "r"(a3), "l"(db));
  } else if constexpr (ACC) {
    asm volatile("wgmma.mma_async.sync.aligned.m64n96k16.f32.bf16.bf16 {" ACC48_REGS
                 "}, {%48,%49,%50,%51}, %52, %53, 1, 1, 0;\n"
                 : ACC48_OPS("+f", d)
                 : "r"(a0), "r"(a1), "r"(a2), "r"(a3), "l"(db), "n"(ACC & 1));
  } else {
    asm volatile("wgmma.mma_async.sync.aligned.m64n96k16.f32.bf16.bf16 {" ACC48_REGS
                 "}, {%48,%49,%50,%51}, %52, 0, 1, 1, 0;\n"
                 : ACC48_OPS("=f", d)
                 : "r"(a0), "r"(a1), "r"(a2), "r"(a3), "l"(db));
  }
}
template <bool ACC>
__device__ __forceinline__ void mma_ss(float (&d)[52], uint64_t da, uint64_t db) {
  if constexpr (ACC) {
    asm volatile("wgmma.mma_async.sync.aligned.m64n104k16.f32.bf16.bf16 " ACC_REGS ", %52, %53, 1, 1, 1, 0, 0;\n"
                 : ACC_OPS("+f", d)
                 : "l"(da), "l"(db));
  } else {
    asm volatile("wgmma.mma_async.sync.aligned.m64n104k16.f32.bf16.bf16 " ACC_REGS ", %52, %53, 0, 1, 1, 0, 0;\n"
                 : ACC_OPS("=f", d)
                 : "l"(da), "l"(db));
  }
}

__device__ __forceinline__ uint64_t desc_sw128(uint32_t saddr) {
  return (uint64_t)((saddr & 0x3FFFF) >> 4) | ((uint64_t)1 << 16) | ((uint64_t)(1024 >> 4) << 32) | ((uint64_t)1 << 62);
}
__device__ __forceinline__ uint64_t desc_p(uint32_t saddr) {
  return (uint64_t)((saddr & 0x3FFFF) >> 4) | ((uint64_t)(128 >> 4) << 16) | ((uint64_t)(kPGrp >> 4) << 32);
}

__device__ __forceinline__ uint32_t pack_bf16(float lo, float hi) {
  uint32_t r;
  asm("cvt.rn.bf16x2.f32 %0, %1, %2;\n" : "=r"(r) : "f"(hi), "f"(lo));
  return r;
}
__device__ __forceinline__ uint32_t pack_bf16_relu(float lo, float hi) {
  uint32_t r;
  asm("cvt.rn.relu.bf16x2.f32 %0, %1, %2;\n" : "=r"(r) : "f"(hi), "f"(lo));
  return r;
}
__device__ __forceinline__ float ex2(float x) {
  float y;
  asm("ex2.approx.ftz.f32 %0, %1;\n" : "=f"(y) : "f"(x));
  return y;
}
__device__ __forceinline__ float rcp(float x) {
  float y;
  asm("rcp.approx.ftz.f32 %0, %1;\n" : "=f"(y) : "f"(x));
  return y;
}
__device__ __forceinline__ void stsm_x4(uint32_t addr, uint32_t r0, uint32_t r1, uint32_t r2, uint32_t r3) {
  asm volatile("stmatrix.sync.aligned.m8n8.x4.shared.b16 [%0], {%1,%2,%3,%4};\n" ::"r"(addr), "r"(r0), "r"(r1), "r"(r2), "r"(r3) : "memory");
}
__device__ __forceinline__ void stsm_x1(uint32_t addr, uint32_t r0) {
  asm volatile("stmatrix.sync.aligned.m8n8.x1.shared.b16 [%0], {%1};\n" ::"r"(addr), "r"(r0) : "memory");
}
__device__ __forceinline__ void stsm_x4_t(uint32_t addr, uint32_t r0, uint32_t r1, uint32_t r2, uint32_t r3) {
  asm volatile("stmatrix.sync.aligned.m8n8.x4.trans.shared.b16 [%0], {%1,%2,%3,%4};\n" ::"r"(addr), "r"(r0), "r"(r1), "r"(r2), "r"(r3) : "memory");
}
__device__ __forceinline__ void stsm_x2_t(uint32_t addr, uint32_t r0, uint32_t r1) {
  asm volatile("stmatrix.sync.aligned.m8n8.x2.trans.shared.b16 [%0], {%1,%2};\n" ::"r"(addr), "r"(r0), "r"(r1) : "memory");
}
__device__ __forceinline__ void ldsm_x4_t(uint32_t addr, uint32_t& r0, uint32_t& r1, uint32_t& r2, uint32_t& r3) {
  asm volatile("ldmatrix.sync.aligned.m8n8.x4.trans.shared.b16 {%0,%1,%2,%3}, [%4];\n" : "=r"(r0), "=r"(r1), "=r"(r2), "=r"(r3) : "r"(addr) : "memory");
}
__device__ __forceinline__ int lds(uint32_t addr) {
  int v;
  asm volatile("ld.shared.u32 %0, [%1];\n" : "=r"(v) : "r"(addr) : "memory");
  return v;
}
__device__ __forceinline__ void mbar_init(uint32_t bar, int count) {
  asm volatile("mbarrier.init.shared::cta.b64 [%0], %1;\n" ::"r"(bar), "r"(count) : "memory");
}
__device__ __forceinline__ void mbar_expect_tx(uint32_t bar, int bytes) {
  asm volatile("mbarrier.arrive.expect_tx.shared::cta.b64 _, [%0], %1;\n" ::"r"(bar), "r"(bytes) : "memory");
}
__device__ __forceinline__ void mbar_wait(uint32_t bar, uint32_t parity) {
  asm volatile(
      "{\n.reg .pred p;\n"
      "WAIT_%=:\n"
      "mbarrier.try_wait.parity.shared::cta.b64 p, [%0], %1;\n"
      "@p bra DONE_%=;\n"
      "bra WAIT_%=;\n"
      "DONE_%=:\n}\n" ::"r"(bar), "r"(parity) : "memory");
}
__device__ __forceinline__ void tma_load_2d(uint32_t dst, const CUtensorMap* tm, int c0, int c1, uint32_t bar) {
  asm volatile("cp.async.bulk.tensor.2d.shared::cluster.global.mbarrier::complete_tx::bytes [%0], [%1, {%3, %4}], [%2];\n" ::"r"(dst),
               "l"(tm), "r"(bar), "r"(c0), "r"(c1) : "memory");
}
__device__ __forceinline__ void tma_load_3d(uint32_t dst, const CUtensorMap* tm, int c1, uint32_t bar) {
  asm volatile("cp.async.bulk.tensor.3d.shared::cluster.global.mbarrier::complete_tx::bytes [%0], [%1, {0, %3, 0}], [%2];\n" ::"r"(dst),
               "l"(tm), "r"(bar), "r"(c1) : "memory");
}
__device__ __forceinline__ bool elect_one() {
  uint32_t p;
  asm volatile("{\n.reg .pred p;\nelect.sync _|p, 0xffffffff;\nselp.u32 %0, 1, 0, p;\n}\n" : "=r"(p));
  return p;
}
__device__ __forceinline__ void tma_store_2d(const CUtensorMap* tm, uint32_t src, int c0, int c1) {
  asm volatile("cp.async.bulk.tensor.2d.global.shared::cta.bulk_group [%0, {%2, %3}], [%1];\n" ::"l"(tm), "r"(src), "r"(c0), "r"(c1) : "memory");
}

template <int N, int FIRST, int S0 = 0, int S1 = 8>
__device__ __forceinline__ void proj(float (&acc)[52], const uint32_t (&w)[32], uint64_t de) {
  wg_fence();
#pragma unroll
  for (int s = S0; s < S1; s++) {
    uint64_t db = de + (uint64_t)(((s >> 2) * N * 128 + (s & 3) * 32) >> 4);
    if (s == 0) mma_rs<N, FIRST>(acc, w[0], w[1], w[2], w[3], db);
    else mma_rs<N, 1>(acc, w[4 * s], w[4 * s + 1], w[4 * s + 2], w[4 * s + 3], db);
  }
  wg_commit();
}
__device__ __forceinline__ void issue_pv(float (&a)[52], const uint32_t (&vf)[28], uint64_t dp) {
  wg_fence();
#pragma unroll
  for (int s = 0; s < 6; s++) mma_rs<104, 1>(a, vf[4 * s], vf[4 * s + 1], vf[4 * s + 2], vf[4 * s + 3], dp + 16 * s);
  mma_rs<104, 1>(a, vf[24], vf[25], vf[26], vf[27], (dp + 16 * 6) & ~((uint64_t)0x3FFF << 16));
  wg_commit();
}
__device__ __forceinline__ void issue_s(float (&acc)[52], uint64_t dq, uint64_t dk) {
  wg_fence();
#pragma unroll
  for (int s = 0; s < 4; s++) {
    if (s == 0) mma_ss<false>(acc, dq, dk);
    else mma_ss<true>(acc, dq + 2 * s, dk + 2 * s);
  }
  wg_commit();
}

__device__ __forceinline__ void sched_barrier() { asm volatile("pmevent 1;\n" ::: "memory"); }
#define PIN(x) asm volatile("" : "+f"(x)::"memory")

constexpr float kC = 0.125f * 1.4426950408889634f;

__device__ __forceinline__ bool out_of_range(float t) { return !(t >= 0x1p-30f && t <= 0x1p30f); }
__device__ __forceinline__ uint32_t mul_bf16x2(uint32_t a, uint32_t b) {
  uint32_t r;
  asm("mul.rn.bf16x2 %0, %1, %2;\n" : "=r"(r) : "r"(a), "r"(b));
  return r;
}
__device__ __forceinline__ float quad_sum(float t) {
  t += __shfl_xor_sync(0xffffffffu, t, 1);
  t += __shfl_xor_sync(0xffffffffu, t, 2);
  return t;
}
struct Q3 { float t, s1, s2, s3; };
__device__ __forceinline__ Q3 q3_start(float t) {
  Q3 q;
  q.t = t;
  q.s1 = __shfl_xor_sync(0xffffffffu, t, 1);
  q.s2 = __shfl_xor_sync(0xffffffffu, t, 2);
  q.s3 = __shfl_xor_sync(0xffffffffu, t, 3);
  return q;
}
__device__ __forceinline__ float q3_end(const Q3& q) { return (q.t + q.s1) + (q.s2 + q.s3); }
template <int O, int J0, int J1>
__device__ __forceinline__ void part_exp(const float (&s)[52], uint32_t (&p)[13], bool tail_invalid, float& t0, float& t1) {
#pragma unroll
  for (int j = J0; j < J1; j++) {
    const int jj = (j + 12) % 13;
    float x = ex2(s[4 * jj + O]), y = ex2(s[4 * jj + O + 1]);
    if (jj == 12 && tail_invalid) { x = 0.f; y = 0.f; }
    p[jj] = pack_bf16(x, y);
    if (j == 0) { t0 = x; t1 = y; } else { t0 += x; t0 += y; }
  }
}
template <int O>
__device__ __forceinline__ float set_max(const float (&s)[52], bool tail_invalid) {
  float m = fmaxf(s[O], s[O + 1]);
#pragma unroll
  for (int j = 1; j < 12; j++) m = fmaxf(m, fmaxf(s[4 * j + O], s[4 * j + O + 1]));
  if (!tail_invalid) m = fmaxf(m, fmaxf(s[48 + O], s[49 + O]));
  m = fmaxf(m, __shfl_xor_sync(0xffffffffu, m, 1));
  return fmaxf(m, __shfl_xor_sync(0xffffffffu, m, 2));
}
template <int O>
__device__ __forceinline__ float set_exact(const float (&s)[52], uint32_t (&p)[13], bool tail_invalid, float m) {
  float t0, t1;
#pragma unroll
  for (int j = 0; j < 13; j++) {
    const int jj = (j + 12) % 13;
    float x = ex2(s[4 * jj + O] - m), y = ex2(s[4 * jj + O + 1] - m);
    if (jj == 12 && tail_invalid) { x = 0.f; y = 0.f; }
    p[jj] = pack_bf16(x, y);
    if (j == 0) { t0 = x; t1 = y; } else { t0 += x; t1 += y; }
  }
  return quad_sum(t0 + t1);
}
__device__ __forceinline__ uint32_t inv2(float t) { const float iv = rcp(t); return pack_bf16(iv, iv); }
template <int C>
__device__ __forceinline__ void part_store(const uint32_t (&p)[13], uint32_t iv, uint32_t paddr) {
  if (C < 3) stsm_x4(paddr + C * 512, mul_bf16x2(p[4 * C], iv), mul_bf16x2(p[4 * C + 1], iv), mul_bf16x2(p[4 * C + 2], iv), mul_bf16x2(p[4 * C + 3], iv));
  else stsm_x1(paddr + 1536, mul_bf16x2(p[12], iv));
}
__device__ __forceinline__ void set_store(const uint32_t (&p)[13], float t, uint32_t paddr) {
  const uint32_t iv = inv2(t);
  part_store<0>(p, iv, paddr);
  part_store<1>(p, iv, paddr);
  part_store<2>(p, iv, paddr);
  part_store<3>(p, iv, paddr);
}

struct Params {
  const uint8_t* w[4];
  uint8_t* out;
  unsigned* claim;
  short n_pairs, n_extra, n_open, streams;
};
struct Maps { CUtensorMap m[8]; };
using I104 = std::integral_constant<int, 104>;
using I96 = std::integral_constant<int, 96>;

__global__ void __launch_bounds__(512, 1)
autoint_kernel(const __grid_constant__ Params prm, const __grid_constant__ Maps tm) {
  extern __shared__ __align__(1024) uint8_t smem[];
  const uint32_t sbase = smem_u32(smem);
  const int tid = threadIdx.x;
  const uint32_t bar_full = sbase + kBarOff;
  const uint32_t bar_w = sbase + kBarOff + 64;
  const int cta = blockIdx.x, stream = cta >> 1, head = cta & 1;
  if (tid >= 256 && tid < 448) {
    if ((tid & 31) == 0) {
      const int k = (tid >> 5) - 8, m = (0x402153 >> (4 * (5 - k))) & 15;
      const uint32_t bar = m == 5 ? bar_full : bar_w + 8 * m;
      const uint32_t dst = sbase + (m == 0 ? kPOff : m == 1 ? kWkOff : m < 4 ? (m + 1) * kEStage : (m - 4) * kEHalf);
      const int c0 = m == 3 ? head * 64 : m == 5 ? 64 : 0, c1 = m < 3 ? head * 128 : m == 3 ? 0 : stream * 2 * kF;
      mbar_init(bar, 1);
      asm volatile("fence.mbarrier_init.release.cluster;\n" ::: "memory");
      fence_async();
      const long long c = clock64();
      while (clock64() - c < k * 60) {}
      mbar_expect_tx(bar, m < 4 ? 16384 : kEHalf);
      tma_load_2d(dst, &tm.m[3 + min(m, 4)], c0, c1, bar);
    }
  } else if (tid == 448) {
    for (int s = 1; s < kStages; s++) mbar_init(bar_full + 8 * s, 1);
    asm volatile("fence.mbarrier_init.release.cluster;\n" ::: "memory");
    asm volatile("st.shared.v2.u32 [%0], {%1,%1};\n" ::"r"(sbase + kZeroOff), "r"(0) : "memory");
    fence_async();
  } else if (tid < 192) {
    if (tid < 96 && (tid & 31) == 0) asm volatile("prefetch.tensormap [%0];\n" ::"l"(&tm.m[tid >> 5]) : "memory");
  } else if (tid >= 224) {
    if (tid < 250) asm volatile("st.shared.v4.u32 [%0], {%1,%1,%1,%1};\nst.shared.v4.u32 [%0 + 16], {%1,%1,%1,%1};\n"
                                ::"r"(sbase + kPOff + 12 * kPGrp + ((tid - 224) >> 1) * 128 + 64 + (tid & 1) * 32), "r"(0) : "memory");
  } else if (tid < 200) {
    asm volatile("prefetch.global.L2 [%0];\n" ::"l"(prm.w[(cta >> 5) & 3] + (cta & 31) * 1024 + (tid & 7) * 128) : "memory");
  }
  const int wg = __shfl_sync(0xffffffffu, tid >> 7, 0);
  __syncthreads();
  sched_barrier();
  const int n_pairs = prm.n_pairs, n_open = prm.n_open, streams = prm.streams;
  const int n_static = 2 * (n_pairs + (stream < prm.n_extra));
  const int n_tiles = n_static + (n_open > 0);
  auto row_of = [&](int i) {
    return i < n_static ? (((i >> 1) * streams + stream) * 2 + (i & 1)) * kF : lds(sbase + kCntOff + 4);
  };
  auto load_e = [&](int i, int st, int row) {
    mbar_expect_tx(bar_full + 8 * st, (i & 1) ? 2 * 96 * 128 : 2 * 104 * 128);
    tma_load_3d(sbase + st * kEStage, &tm.m[i & 1], row + (i & 1) * 4, bar_full + 8 * st);
  };
  auto next_row = [&](int i, int row) { return row + ((i & 1) ? (2 * streams - 1) * kF : kF); };
  auto read_count = [&]() { return __shfl_sync(0xffffffffu, lds(sbase + kCntOff), 0); };

#define ROLE_IDS()                                                                                     \
  int rtid;                                                                                            \
  asm volatile("mov.u32 %0, %tid.x;\n" : "=r"(rtid));                                                  \
  const int lane = rtid & 31;                                                                          \
  [[maybe_unused]] const int warp = __shfl_sync(0xffffffffu, (rtid >> 5) & 3, 0);                      \
  [[maybe_unused]] const uint32_t chunk = ((rtid >> 4) & 6) + ((lane >> 3) & 1);                       \
  [[maybe_unused]] const uint32_t t_off = ((lane >> 4) * 8 + (lane & 7)) * 128 + ((chunk ^ (lane & 7)) << 4)
  auto load_frags = [&](uint32_t (&w)[32], int m, uint32_t addr) {
    mbar_wait(bar_w + 8 * m, 0);
#pragma unroll
    for (int s = 0; s < 8; s++) ldsm_x4_t(addr + s * 2048, w[4 * s], w[4 * s + 1], w[4 * s + 2], w[4 * s + 3]);
  };
  const uint64_t dE0 = desc_sw128(sbase);
  auto finish = [&](int n_items) {
    int rtid;
    asm volatile("mov.u32 %0, %tid.x;\n" : "=r"(rtid));
    uint8_t* dst = prm.out + (size_t)row_of(n_items - 1) * (kD * 2) + head * 128;
    bar_sync(BAR_W, 512);
#pragma unroll
    for (int k = 0; k < 2; k++) {
      const int c = rtid + 512 * k, r = c >> 3;
      if (c < 8 * kF) {
        uint4 v;
        asm volatile("ld.shared.v4.u32 {%0,%1,%2,%3}, [%4];\n" : "=r"(v.x), "=r"(v.y), "=r"(v.z), "=r"(v.w)
                     : "r"(sbase + kOOff + r * 128 + (((c ^ r) & 7) << 4)) : "memory");
        *(uint4*)(dst + r * (kD * 2) + (c & 7) * 16) = v;
      }
    }
  };

  if (wg == 0) {
    asm volatile("setmaxnreg.inc.sync.aligned.u32 144;\n");
    ROLE_IDS();
    uint32_t wQ[32], wK[32];
    float acc[52];
    load_frags(wQ, 0, sbase + kPOff + t_off);
#pragma unroll
    for (int i = 0; i < 32; i++) wQ[i] = pack_bf16(__uint_as_float(wQ[i] << 16) * kC, __uint_as_float(wQ[i] & 0xffff0000u) * kC);
    int n_items = n_static;
    const uint32_t k_addr = sbase + kKOff + t_off, q_addr = sbase + kQOff + t_off, q_hi = q_addr + (lane & 16) * 64;
    uint32_t pk[26];
    uint32_t e_off = 0, e_bar = bar_full, e_ph = 0;
    auto pack = [&](auto NC) {
      constexpr int N = decltype(NC)::value;
      wg_wait<0>();
      fence_acc<N>(acc);
#pragma unroll
      for (int i = 0; i < N / 4; i++) pk[i] = pack_bf16(acc[2 * i], acc[2 * i + 1]);
    };
    auto publish = [&](int it) {
      const int n = it >= 2 ? 384 : 256;
      fence_async();
      bar_arrive(BAR_X, n);
      bar_arrive(BAR_X + 1, n);
    };
    auto item = [&](auto NC, auto FC, int it) {
      constexpr int N = decltype(NC)::value;
      constexpr bool first = decltype(FC)::value;
      constexpr int kPre = first ? 4 : 8;
      const uint64_t dE = dE0 + e_off;
      auto store_q = [&](int j0, int j1) {
#pragma unroll
        for (int j = j0; j < j1; j += 2) {
          if (j < 8) stsm_x4_t(q_addr + j * 1024, pk[2 * j], pk[2 * j + 1], pk[2 * j + 2], pk[2 * j + 3]);
          else if (j < 12) stsm_x4_t(q_hi + (2 * j - 8) * 1024, pk[2 * j], pk[2 * j + 1], pk[2 * j + 2], pk[2 * j + 3]);
          else if (N == 104) {
            stsm_x4_t(q_hi + 9 * 1024, pk[24], pk[25], pk[24], pk[25]);
            stsm_x4_t(q_hi + 13 * 1024, pk[24], pk[25], pk[24], pk[25]);
          }
        }
      };
      if (first) {
        mbar_wait(bar_w + 32, 0);
        proj<N, 0, 0, 4>(acc, wQ, dE);
        bar_arrive(BAR_T1, 256);
        load_frags(wK, 1, q_addr + (kWkOff - kQOff));
        mbar_wait(bar_full, 0);
        proj<N, 0, 4, 8>(acc, wQ, dE);
        bar_arrive(BAR_S1, 256);
      } else {
        if (it >= 3) bar_sync(BAR_T1, 256);
        proj<N, 0>(acc, wQ, dE);
        if (N == 104 || it > 1) publish(it - 1);
        else bar_arrive(BAR_X + 1, 256);
      }
      pack(NC);
#pragma unroll
      for (int i = 0; i < N / 4; i++) asm volatile("" : "+r"(pk[i])::"memory");
      sched_barrier();
      if (!first) bar_sync(BAR_QE, 256);
      store_q(0, kPre);
      if (!first) bar_sync(BAR_SP + 1, 256);
      proj<N, 2>(acc, wK, dE);
      if (N == 104 && !first && it == 2) bar_arrive(BAR_S2, 256);
      if (first) bar_arrive(BAR_O, 256);
      store_q(kPre, 8);
      e_off += kEStage >> 4;
      e_bar += 8;
      if (e_off == kStages * (kEStage >> 4)) { e_off = 0; e_bar = bar_full; e_ph ^= 1; }
      if (!first) {
        if (it + 1 < n_tiles) mbar_wait(e_bar, e_ph);
        bar_sync(BAR_QE + 1, 256);
      }
      store_q(8, 14);
      if (N == 96 && it + 1 == n_static) n_items = read_count();
      pack(NC);
#pragma unroll
      for (int j = 0; j < 12; j += 2) stsm_x4_t(k_addr + j * 1024, pk[2 * j], pk[2 * j + 1], pk[2 * j + 2], pk[2 * j + 3]);
      if (N == 104) stsm_x2_t(k_addr + 12 * 1024, pk[24], pk[25]);
      if (first) {
        fence_async();
        bar_arrive(BAR_X, 256);
        mbar_wait(bar_full + 8, 0);
        bar_sync(BAR_SP, 256);
      }
    };
    item(I104{}, std::true_type{}, 0);
    for (int it = 1;; it += 2) {
      item(I96{}, std::false_type{}, it);
      if (it + 1 == n_items) break;
      item(I104{}, std::false_type{}, it + 1);
      if (it + 2 == n_items) break;
    }
    publish(n_items - 1);
    finish(n_items);
  } else if (wg == 1) {
    asm volatile("setmaxnreg.inc.sync.aligned.u32 176;\n");
    ROLE_IDS();
    uint32_t wV[32], wR[32];
    float acc[52];
    uint32_t vf[28], pl[2];
    asm volatile("ld.volatile.shared.v2.u32 {%0, %1}, [%2];\n" : "=r"(vf[26]), "=r"(vf[27]) : "r"(sbase + kZeroOff) : "memory");
    load_frags(wV, 2, sbase + 3 * kEStage + t_off);
    int n_items = n_static;
    const uint32_t o_even = sbase + kOOff + t_off;
    const uint32_t r4 = (lane & 7) + 4;
    const uint32_t o_odd = sbase + kOOff + ((lane >> 4) * 8 + r4) * 128 + ((chunk ^ (r4 & 7)) << 4) + vf[26];
    const uint32_t o_odd_last = sbase + kOOff + ((lane & 4) ? (r4 & 7) : 96 + r4) * 128 + ((chunk ^ (r4 & 7)) << 4) + vf[26];
    const uint64_t dP = desc_p(sbase + kPOff);
    uint32_t e_off = 0;
    auto store_o = [&](int par, int it, int j0 = 0, int j1 = 14) {
      const uint32_t a = par ? o_odd : o_even;
      if (j0 == 0 && it >= 1) bar_sync(BAR_OF, 160);
#pragma unroll
      for (int j = j0; j < j1; j += 2) {
        if (j < 12) stsm_x4_t(a + j * 1024, vf[2 * j], vf[2 * j + 1], vf[2 * j + 2], vf[2 * j + 3]);
        else stsm_x2_t(par ? o_odd_last : o_even + 12 * 1024, pl[0], pl[1]);
      }
    };
    auto item = [&](auto NC, auto FC, int it) {
      constexpr int N = decltype(NC)::value, par = N == 96;
      constexpr bool first = decltype(FC)::value;
      const uint64_t dE = dE0 + e_off;
      if (first) {
        mbar_wait(bar_w + 32, 0);
        bar_sync(BAR_T1, 256);
        proj<N, 0, 0, 4>(acc, wV, dE);
        mbar_wait(bar_full, 0);
        bar_sync(BAR_S1, 256);
        proj<N, 0, 4, 8>(acc, wV, dE);
        load_frags(wR, 3, o_even + (4 * kEStage - kOOff));
        bar_arrive(BAR_W, 160);
      } else {
#pragma unroll
        for (int i = 0; i < 24; i++) asm volatile("" : "+r"(vf[i])::"memory");
        asm volatile("" : "+r"(pl[0]), "+r"(pl[1])::"memory");
        sched_barrier();
        if (it + 1 < n_items) bar_sync(BAR_SP, 256);
        proj<N, 2>(acc, wV, dE);
        if (it + 1 < n_items) bar_arrive(BAR_X + 1, 384);
        store_o(par ^ 1, it - 1, 0, 4);
        bar_sync(BAR_PF + par, 384);
        fence_async();
        if (par && it + 3 == n_static) n_items = read_count();
        store_o(par ^ 1, it - 1, 4, 14);
        bar_arrive(BAR_O, 160);
      }
      wg_wait<0>();
      fence_acc<N>(acc);
#pragma unroll
      for (int i = 0; i < N / 4; i++) {
        if (!first) asm("cvt.rn.bf16x2.f32 %0, %1, %2;\n" : "+r"(vf[i]) : "f"(acc[2 * i + 1]), "f"(acc[2 * i]));
        else vf[i] = pack_bf16(acc[2 * i], acc[2 * i + 1]);
      }
      if (first) bar_sync(BAR_O, 256);
      proj<N, 2>(acc, wR, dE);
      if (first) {
        bar_sync(BAR_PF + par, 384);
        fence_async();
        bar_sync(BAR_SP, 256);
        bar_sync(BAR_S2, 256);
      }
      issue_pv(acc, vf, dP + (uint64_t)((par * kPBuf) >> 4));
      if (it + 3 < n_items) bar_arrive(BAR_T1, 256);
      e_off = e_off == (kStages - 1) * (kEStage >> 4) ? 0 : e_off + (kEStage >> 4);
      wg_wait<0>();
      if (it + 2 < n_items) bar_arrive(BAR_X, 384);
      sched_barrier();
      fence_acc(acc);
#pragma unroll
      for (int i = 0; i < 24; i++) asm("cvt.rn.relu.bf16x2.f32 %0, %1, %2;\n" : "+r"(vf[i]) : "f"(acc[2 * i + 1]), "f"(acc[2 * i]));
      pl[0] = pack_bf16_relu(acc[48], acc[49]);
      pl[1] = pack_bf16_relu(acc[50], acc[51]);
    };
    item(I104{}, std::true_type{}, 0);
    for (int it = 1;; it += 2) {
      item(I96{}, std::false_type{}, it);
      if (it + 1 == n_items) break;
      item(I104{}, std::false_type{}, it + 1);
      if (it + 2 == n_items) break;
    }
    store_o((n_items - 1) & 1, n_items - 1);
    finish(n_items);
  } else {
    asm volatile("setmaxnreg.dec.sync.aligned.u32 96;\n");
    ROLE_IDS();
    const uint64_t dK = desc_sw128(sbase + kKOff);
    float acc[52];
    if (wg == 2) {
      const uint64_t dQ = desc_sw128(sbase + kQOff);
      uint32_t pa = sbase + kPOff + 2 * warp * kPGrp + lane * 16;
      int tail = (lane >> 1) & 1;
      if (rtid == 256) {
        mbar_wait(bar_w, 0);
        load_e(1, 1, row_of(1));
        mbar_wait(bar_full, 0);
        load_e(2, 2, row_of(2));
      }
      if (rtid == 320) {
        const int m = max(n_open, 1), x = stream % m;
        asm volatile("st.shared.v4.u32 [%0], {%1,%2,%3,%4};\n" ::"r"(sbase + kCntOff), "r"(n_static), "r"((2 * n_pairs * streams + x) * kF),
                     "r"(2 * x + head), "r"((streams - 1 - x) / m) : "memory");
      }
      if (warp == kServe) bar_sync(BAR_W, 160);
      __syncwarp();
      int n_items = n_static;
      int ld_row = (2 * (streams + stream) + 1) * kF, ld_st = 3;
      for (int it = 0; it < n_items; it++) {
        bar_sync(BAR_X, it >= 2 ? 384 : 256);
        issue_s(acc, dQ, dK);
        bar_arrive(BAR_SP, 256);
        if (warp == kServe && it + 3 < n_tiles) {
          if (it + 3 == n_static) ld_row = __shfl_sync(0xffffffffu, lds(sbase + kCntOff + 4), 0);
          if (elect_one()) load_e(it + 3, ld_st, ld_row);
        }
        ld_row = next_row(it + 3, ld_row);
        ld_st = ld_st == kStages - 1 ? 0 : ld_st + 1;
        if (it + 1 == n_static) n_items = read_count();
        wg_wait<0>();
        if (it + 1 < n_items) bar_arrive(BAR_QE, 256);
        sched_barrier();
        fence_acc(acc);
        uint32_t p0[13], p1[13];
        float t0, t1, u0, u1;
        part_exp<0, 0, 13>(acc, p0, tail, t0, u0);
        part_exp<2, 0, 2>(acc, p1, tail, t1, u1);
        t0 += u0;
        u0 = __shfl_xor_sync(0xffffffffu, t0, 1);
        PIN(t1); PIN(u1);
        sched_barrier();
        part_exp<2, 2, 6>(acc, p1, tail, t1, u1);
        PIN(t1); PIN(u1);
        sched_barrier();
        t0 += u0;
        u0 = __shfl_xor_sync(0xffffffffu, t0, 2);
        sched_barrier();
        part_exp<2, 6, 10>(acc, p1, tail, t1, u1);
        PIN(t1); PIN(u1);
        sched_barrier();
        t0 += u0;
        const uint32_t i0 = inv2(t0);
        part_exp<2, 10, 13>(acc, p1, tail, t1, u1);
        part_store<0>(p0, i0, pa);
        const Q3 q1 = q3_start(t1 + u1);
        sched_barrier();
        part_store<1>(p0, i0, pa);
        part_store<2>(p0, i0, pa);
        part_store<3>(p0, i0, pa);
        sched_barrier();
        t1 = q3_end(q1);
        if (__builtin_expect(__any_sync(0xffffffffu, out_of_range(t0) || out_of_range(t1)), 0)) {
          set_store(p0, set_exact<0>(acc, p0, tail, set_max<0>(acc, tail)), pa);
          t1 = set_exact<2>(acc, p1, tail, set_max<2>(acc, tail));
        }
        set_store(p1, t1, pa + kPGrp);
        bar_arrive(BAR_PF + (it & 1), 384);
        pa += (it & 1) ? -kPBuf : kPBuf;
        tail ^= 1;
      }
      finish(n_items);
    } else {
      const uint64_t dQ = desc_sw128(sbase + kQOff + 8192);
      const bool server = warp == kServe;
      auto serve = [&](int it, int row) {
        bar_sync(BAR_O, 160);
        if (elect_one()) {
          fence_async();
          tma_store_2d(&tm.m[2], sbase + kOOff, head * 64, row);
          asm volatile("cp.async.bulk.commit_group;\n" ::: "memory");
        }
      };
      auto release_o = [&]() {
        asm volatile("cp.async.bulk.wait_group.read 0;\n" ::: "memory");
        __syncwarp();
        bar_arrive(BAR_OF, 160);
      };
      uint32_t pa = sbase + kPOff + (8 + warp) * kPGrp + lane * 16;
      const uint32_t trash = sbase + kTrashOff + lane * 16;
      const uint32_t pd = sbase + kPOff + 12 * kPGrp + (3 * warp + (lane >> 3)) * 128 + (lane & 7) * 16 + ((lane >> 2) & 1) * kPBuf;
      const bool exists = lane < 24 || warp == 3;
      uint32_t pd0 = exists && !(lane & 4) ? pd : trash, pd1 = exists && (lane & 4) ? pd : trash;
      const uint32_t sum_addr = sbase + kSumOff + (lane >> 2) * 16;
      int tail = (lane >> 1) & 1, other = lane >> 4;
      int n_items = n_static;
      uint32_t ticket = 1;
      int st_row = 2 * (stream - streams) * kF;
      for (int it = 0; it < n_items; it++) {
        bar_sync(BAR_X + 1, it >= 2 ? 384 : 256);
        issue_s(acc, dQ, dK);
        if (it + 1 < n_items) bar_arrive(BAR_SP + 1, 256);
        if (it + 2 == n_static) n_items = read_count();
        wg_wait<0>();
        if (it + 1 < n_items) bar_arrive(BAR_QE + 1, 256);
        if (server && it >= 2) serve(it - 2, st_row);
        st_row = next_row(it, st_row);
        if (ticket == 0) asm volatile("st.shared.u32 [%0], %1;\n" ::"r"(sbase + kCntOff), "r"(n_static + 1) : "memory");
        sched_barrier();
        fence_acc(acc);
        uint32_t p0[13], d[4];
        float td;
        auto d_exp = [&](auto WC, auto SC, float m) {
          constexpr int W = decltype(WC)::value;
          constexpr bool SUB = decltype(SC)::value;
          float x[8];
#pragma unroll
          for (int k = 0; k < (W == 3 ? 8 : 6); k++) {
            const float v = acc[4 * (3 * W + (k >> 1)) + 2 + (k & 1)];
            x[k] = ex2(SUB ? v - m : v);
          }
          td = ((x[0] + x[1]) + (x[2] + x[3])) + (x[4] + x[5]);
          if (W == 3) {
            if (tail) { x[6] = 0.f; x[7] = 0.f; }
            td += x[6] + x[7];
            d[3] = pack_bf16(x[6], x[7]);
          } else d[3] = 0;
#pragma unroll
          for (int k = 0; k < 3; k++) d[k] = pack_bf16(x[2 * k], x[2 * k + 1]);
        };
        auto d_exp_w = [&](auto SC, float m) {
          if (warp == 0) d_exp(std::integral_constant<int, 0>{}, SC, m);
          else if (warp == 1) d_exp(std::integral_constant<int, 1>{}, SC, m);
          else if (warp == 2) d_exp(std::integral_constant<int, 2>{}, SC, m);
          else d_exp(std::integral_constant<int, 3>{}, SC, m);
        };
        d_exp_w(std::false_type{}, 0.f);
        float t0, u0, ud = __shfl_xor_sync(0xffffffffu, td, 1);
        sched_barrier();
        part_exp<0, 0, 4>(acc, p0, tail, t0, u0);
        PIN(t0); PIN(u0);
        sched_barrier();
        td += ud;
        ud = __shfl_xor_sync(0xffffffffu, td, 2);
        sched_barrier();
        part_exp<0, 4, 8>(acc, p0, tail, t0, u0);
        PIN(t0); PIN(u0);
        sched_barrier();
        asm volatile("st.shared.f32 [%0], %1;\n" ::"r"(sum_addr + warp * 4), "f"(td + ud) : "memory");
        sched_barrier();
        part_exp<0, 8, 13>(acc, p0, tail, t0, u0);
        const Q3 q0 = q3_start(t0 + u0);
        bar_sync(BAR_D, 128);
        float4 u;
        asm volatile("ld.shared.v4.f32 {%0,%1,%2,%3}, [%4];\n" : "=f"(u.x), "=f"(u.y), "=f"(u.z), "=f"(u.w) : "r"(sum_addr) : "memory");
        sched_barrier();
        t0 = q3_end(q0);
        set_store(p0, t0, pa);
        td = (u.x + u.y) + (u.z + u.w);
        if (__builtin_expect(__any_sync(0xffffffffu, out_of_range(t0) | (!other & out_of_range(td))), 0)) {
          set_store(p0, set_exact<0>(acc, p0, tail, set_max<0>(acc, tail)), pa);
          const float m = set_max<2>(acc, tail);
          d_exp_w(std::true_type{}, m);
          td = set_exact<2>(acc, p0, tail, m);
        }
        const uint32_t iv = inv2(td);
        stsm_x4(pd0, mul_bf16x2(d[0], iv), mul_bf16x2(d[1], iv), mul_bf16x2(d[2], iv), mul_bf16x2(d[3], iv));
        bar_arrive(BAR_PF + (it & 1), 384);
        if (server && it >= 2) release_o();
        ticket = 1;
        if (it + 4 == n_static && n_open > 0 && rtid == 384 + 32 * kClaim)
          asm volatile("atom.global.inc.u32 %0, [%1], %2;\n" : "=r"(ticket) : "l"(prm.claim + lds(sbase + kCntOff + 8)), "r"(lds(sbase + kCntOff + 12)) : "memory");
        pa += (it & 1) ? -kPBuf : kPBuf;
        tail ^= 1;
        other ^= 1;
        const uint32_t x = pd0; pd0 = pd1; pd1 = x;
      }
      if (server) {
        serve(n_items - 2, st_row);
        release_o();
      }
      finish(n_items);
    }
  }
}

typedef CUresult (*EncodeFn)(CUtensorMap*, CUtensorMapDataType, cuuint32_t, void*, const cuuint64_t*, const cuuint64_t*,
                             const cuuint32_t*, const cuuint32_t*, CUtensorMapInterleave, CUtensorMapSwizzle,
                             CUtensorMapL2promotion, CUtensorMapFloatOOBfill);

}

extern "C" void kernel_launch(void* const* d_in, const int* in_sizes, int n_in, void* d_out, int out_size) {
  static EncodeFn encode = nullptr;
  static int num_sms = 0;
  static unsigned* claim = nullptr;
  if (!encode) {
    void* fn = nullptr;
    cudaDriverEntryPointQueryResult qres;
    cudaGetDriverEntryPoint("cuTensorMapEncodeTiled", &fn, cudaEnableDefault, &qres);
    encode = (EncodeFn)fn;
    int dev = 0;
    cudaGetDevice(&dev);
    cudaDeviceGetAttribute(&num_sms, cudaDevAttrMultiProcessorCount, dev);
    cudaGetSymbolAddress((void**)&claim, g_claim);
    cudaFuncSetAttribute(autoint_kernel, cudaFuncAttributeMaxDynamicSharedMemorySize, kSmemBytes);
  }
  auto make = [&](void* p, uint64_t cols, uint64_t rows, uint32_t box_rows, CUtensorMapL2promotion promo) {
    CUtensorMap tm;
    cuuint64_t dims[2] = {cols, rows};
    cuuint64_t strides[1] = {cols * 2};
    cuuint32_t box[2] = {64, box_rows};
    cuuint32_t estr[2] = {1, 1};
    encode(&tm, CU_TENSOR_MAP_DATA_TYPE_BFLOAT16, 2, p, dims, strides, box, estr, CU_TENSOR_MAP_INTERLEAVE_NONE,
           CU_TENSOR_MAP_SWIZZLE_128B, promo, CU_TENSOR_MAP_FLOAT_OOB_FILL_NONE);
    return tm;
  };
  Maps tm;
  for (int i = 0; i < 2; i++) {
    cuuint64_t dims[3] = {64, (cuuint64_t)kB * kF, 2};
    cuuint64_t strides[2] = {kD * 2, 128};
    cuuint32_t box[3] = {64, i ? 96u : 104u, 2};
    cuuint32_t estr[3] = {1, 1, 1};
    encode(&tm.m[i], CU_TENSOR_MAP_DATA_TYPE_BFLOAT16, 3, d_in[0], dims, strides, box, estr, CU_TENSOR_MAP_INTERLEAVE_NONE,
           CU_TENSOR_MAP_SWIZZLE_128B, CU_TENSOR_MAP_L2_PROMOTION_L2_256B, CU_TENSOR_MAP_FLOAT_OOB_FILL_NONE);
  }
  tm.m[2] = make(d_out, kD, (uint64_t)kB * kF, kF, CU_TENSOR_MAP_L2_PROMOTION_NONE);
  for (int i = 0; i < 3; i++) tm.m[3 + i] = make(d_in[1 + i], 64, 256, 128, CU_TENSOR_MAP_L2_PROMOTION_L2_256B);
  tm.m[6] = make(d_in[4], 128, 128, 128, CU_TENSOR_MAP_L2_PROMOTION_L2_256B);
  tm.m[7] = make(d_in[0], kD, (uint64_t)kB * kF, 104, CU_TENSOR_MAP_L2_PROMOTION_L2_128B);
  const int grid = (num_sms < 2 ? 2 : num_sms > 256 ? 256 : num_sms) & ~1, streams = grid / 2;
  const int n_pairs = kB / 2 / streams, rem = kB / 2 - n_pairs * streams;
  const bool open = 2 * rem <= streams;
  Params prm;
  for (int i = 0; i < 4; i++) prm.w[i] = (const uint8_t*)d_in[1 + i];
  prm.out = (uint8_t*)d_out;
  prm.claim = claim;
  prm.n_pairs = (short)n_pairs;
  prm.n_extra = (short)(open ? 0 : rem);
  prm.n_open = (short)(open ? 2 * rem : 0);
  prm.streams = (short)streams;
  autoint_kernel<<<grid, 512, kSmemBytes>>>(prm, tm);
}
```

```cpp
#include <cuda_runtime.h>
#include <cuda_bf16.h>
#include <cuda.h>
#include <stdint.h>
#include <type_traits>

namespace {

constexpr int kB = 4096, kF = 100, kD = 128;
constexpr int kStages = 5;
constexpr int kServe = 1, kStore = 2, kClaim = 3;
constexpr int kRs = 2;
constexpr int kEHalf = 104 * 128;
constexpr int kEStage = 2 * kEHalf;
constexpr int kQOff = kStages * kEStage;
constexpr int kKOff = kQOff + 13312;
constexpr int kPOff = kKOff + 16384;
constexpr int kPGrp = 13 * 128;
constexpr int kPBuf = 13 * kPGrp;
constexpr int kWkOff = kPOff + 22528;
constexpr int kOOff = kPOff + 44032;
constexpr int kBarOff = kOOff + 13312;
constexpr int kTrashOff = kBarOff + 128;
constexpr int kSumOff = kTrashOff + 1920;
constexpr int kMaxOff = kSumOff + 1024;
constexpr int kZeroOff = kMaxOff + 768;
constexpr int kCntOff = kZeroOff + 16;
constexpr int kSmemBytes = kZeroOff + 128;
static_assert(kSumOff % 512 == 0 && kQOff % 1024 == 0 && kKOff % 1024 == 0 && kPOff % 1024 == 0 && kOOff % 1024 == 0 && kWkOff % 1024 == 0 &&
              2 * kPBuf <= 44032 && kWkOff >= kPOff + kPBuf && kWkOff + 16384 <= kOOff && kSmemBytes <= 232448, "smem layout");

enum {
  BAR_T1 = 1,
  BAR_X = 2,
  BAR_QE = 4,
  BAR_PF = 6,
  BAR_O = 8,
  BAR_S2 = 9,
  BAR_W = 10,
  BAR_SP = 11,
  BAR_OF = 13,
  BAR_D = 14,
  BAR_S1 = 15
};

__device__ unsigned g_claim[256];

__device__ __forceinline__ uint32_t smem_u32(const void* p) { return (uint32_t)__cvta_generic_to_shared(p); }

__device__ __forceinline__ void wg_fence() { asm volatile("wgmma.fence.sync.aligned;\n" ::: "memory"); }
__device__ __forceinline__ void wg_commit() { asm volatile("wgmma.commit_group.sync.aligned;\n" ::: "memory"); }
template <int N> __device__ __forceinline__ void wg_wait() { asm volatile("wgmma.wait_group.sync.aligned %0;\n" ::"n"(N) : "memory"); }
__device__ __forceinline__ void fence_async() { asm volatile("fence.proxy.async.shared::cta;\n" ::: "memory"); }
__device__ __forceinline__ void bar_sync(int id, int n) { asm volatile("bar.sync %0, %1;\n" ::"r"(id), "r"(n) : "memory"); }
__device__ __forceinline__ void bar_arrive(int id, int n) { asm volatile("bar.arrive %0, %1;\n" ::"r"(id), "r"(n) : "memory"); }

#define ACC48_REGS "%0,%1,%2,%3,%4,%5,%6,%7,%8,%9,%10,%11,%12,%13,%14,%15,%16,%17,%18,%19,%20,%21,%22,%23,%24,%25," \
                   "%26,%27,%28,%29,%30,%31,%32,%33,%34,%35,%36,%37,%38,%39,%40,%41,%42,%43,%44,%45,%46,%47"
#define ACC_REGS "{" ACC48_REGS ",%48,%49,%50,%51}"
#define ACC48_OPS(c, d)                                                                                      \
  c(d[0]), c(d[1]), c(d[2]), c(d[3]), c(d[4]), c(d[5]), c(d[6]), c(d[7]), c(d[8]), c(d[9]), c(d[10]),        \
  c(d[11]), c(d[12]), c(d[13]), c(d[14]), c(d[15]), c(d[16]), c(d[17]), c(d[18]), c(d[19]), c(d[20]),        \
  c(d[21]), c(d[22]), c(d[23]), c(d[24]), c(d[25]), c(d[26]), c(d[27]), c(d[28]), c(d[29]), c(d[30]),        \
  c(d[31]), c(d[32]), c(d[33]), c(d[34]), c(d[35]), c(d[36]), c(d[37]), c(d[38]), c(d[39]), c(d[40]),        \
  c(d[41]), c(d[42]), c(d[43]), c(d[44]), c(d[45]), c(d[46]), c(d[47])
#define ACC_OPS(c, d) ACC48_OPS(c, d), c(d[48]), c(d[49]), c(d[50]), c(d[51])

template <int N = 104>
__device__ __forceinline__ void fence_acc(float (&d)[52]) {
  if constexpr (N == 104) asm volatile("" : ACC_OPS("+f", d)::"memory");
  else asm volatile("" : ACC48_OPS("+f", d)::"memory");
}

template <int N, int ACC>
__device__ __forceinline__ void mma_rs(float (&d)[52], uint32_t a0, uint32_t a1, uint32_t a2, uint32_t a3, uint64_t db) {
  if constexpr (N == 104 && ACC) {
    asm volatile("wgmma.mma_async.sync.aligned.m64n104k16.f32.bf16.bf16 " ACC_REGS
                 ", {%52,%53,%54,%55}, %56, %57, 1, 1, 0;\n"
                 : ACC_OPS("+f", d)
                 : "r"(a0), "r"(a1), "r"(a2), "r"(a3), "l"(db), "n"(ACC & 1));
  } else if constexpr (N == 104) {
    asm volatile("wgmma.mma_async.sync.aligned.m64n104k16.f32.bf16.bf16 " ACC_REGS
                 ", {%52,%53,%54,%55}, %56, 0, 1, 1, 0;\n"
                 : ACC_OPS("=f", d)
                 : "r"(a0), "r"(a1), "r"(a2), "r"(a3), "l"(db));
  } else if constexpr (ACC) {
    asm volatile("wgmma.mma_async.sync.aligned.m64n96k16.f32.bf16.bf16 {" ACC48_REGS
                 "}, {%48,%49,%50,%51}, %52, %53, 1, 1, 0;\n"
                 : ACC48_OPS("+f", d)
                 : "r"(a0), "r"(a1), "r"(a2), "r"(a3), "l"(db), "n"(ACC & 1));
  } else {
    asm volatile("wgmma.mma_async.sync.aligned.m64n96k16.f32.bf16.bf16 {" ACC48_REGS
                 "}, {%48,%49,%50,%51}, %52, 0, 1, 1, 0;\n"
                 : ACC48_OPS("=f", d)
                 : "r"(a0), "r"(a1), "r"(a2), "r"(a3), "l"(db));
  }
}
template <bool ACC>
__device__ __forceinline__ void mma_ss(float (&d)[52], uint64_t da, uint64_t db) {
  if constexpr (ACC) {
    asm volatile("wgmma.mma_async.sync.aligned.m64n104k16.f32.bf16.bf16 " ACC_REGS ", %52, %53, 1, 1, 1, 0, 0;\n"
                 : ACC_OPS("+f", d)
                 : "l"(da), "l"(db));
  } else {
    asm volatile("wgmma.mma_async.sync.aligned.m64n104k16.f32.bf16.bf16 " ACC_REGS ", %52, %53, 0, 1, 1, 0, 0;\n"
                 : ACC_OPS("=f", d)
                 : "l"(da), "l"(db));
  }
}

#define ACC20_OPS(c, d)                                                                                      \
  c(d[0]), c(d[1]), c(d[2]), c(d[3]), c(d[4]), c(d[5]), c(d[6]), c(d[7]), c(d[8]), c(d[9]), c(d[10]),        \
  c(d[11]), c(d[12]), c(d[13]), c(d[14]), c(d[15]), c(d[16]), c(d[17]), c(d[18]), c(d[19])
#define ACC20_REGS "{%0,%1,%2,%3,%4,%5,%6,%7,%8,%9,%10,%11,%12,%13,%14,%15,%16,%17,%18,%19}"
template <bool ACC>
__device__ __forceinline__ void mma_rs40(float (&d)[20], const uint32_t* a, uint64_t db) {
  if constexpr (ACC) {
    asm volatile("wgmma.mma_async.sync.aligned.m64n40k16.f32.bf16.bf16 " ACC20_REGS ", {%20,%21,%22,%23}, %24, 1, 1, 1, 0;\n"
                 : ACC20_OPS("+f", d) : "r"(a[0]), "r"(a[1]), "r"(a[2]), "r"(a[3]), "l"(db));
  } else {
    asm volatile("wgmma.mma_async.sync.aligned.m64n40k16.f32.bf16.bf16 " ACC20_REGS ", {%20,%21,%22,%23}, %24, 0, 1, 1, 0;\n"
                 : ACC20_OPS("=f", d) : "r"(a[0]), "r"(a[1]), "r"(a[2]), "r"(a[3]), "l"(db));
  }
}

__device__ __forceinline__ void mma_ss40(float (&d)[20], uint64_t da, uint64_t db) {
  asm volatile("wgmma.mma_async.sync.aligned.m64n40k16.f32.bf16.bf16 " ACC20_REGS ", %20, %21, 1, 1, 1, 0, 0;\n" : ACC20_OPS("+f", d) : "l"(da), "l"(db));
}

__device__ __forceinline__ uint64_t desc_sw128(uint32_t saddr) {
  return (uint64_t)((saddr & 0x3FFFF) >> 4) | ((uint64_t)1 << 16) | ((uint64_t)(1024 >> 4) << 32) | ((uint64_t)1 << 62);
}
__device__ __forceinline__ uint64_t desc_p(uint32_t saddr) {
  return (uint64_t)((saddr & 0x3FFFF) >> 4) | ((uint64_t)(128 >> 4) << 16) | ((uint64_t)(kPGrp >> 4) << 32);
}

__device__ __forceinline__ uint32_t pack_bf16(float lo, float hi) {
  uint32_t r;
  asm("cvt.rn.bf16x2.f32 %0, %1, %2;\n" : "=r"(r) : "f"(hi), "f"(lo));
  return r;
}
__device__ __forceinline__ uint32_t pack_bf16_relu(float lo, float hi) {
  uint32_t r;
  asm("cvt.rn.relu.bf16x2.f32 %0, %1, %2;\n" : "=r"(r) : "f"(hi), "f"(lo));
  return r;
}
__device__ __forceinline__ float ex2(float x) {
  float y;
  asm("ex2.approx.ftz.f32 %0, %1;\n" : "=f"(y) : "f"(x));
  return y;
}
__device__ __forceinline__ float rcp(float x) {
  float y;
  asm("rcp.approx.ftz.f32 %0, %1;\n" : "=f"(y) : "f"(x));
  return y;
}
__device__ __forceinline__ void stsm_x4(uint32_t addr, uint32_t r0, uint32_t r1, uint32_t r2, uint32_t r3) {
  asm volatile("stmatrix.sync.aligned.m8n8.x4.shared.b16 [%0], {%1,%2,%3,%4};\n" ::"r"(addr), "r"(r0), "r"(r1), "r"(r2), "r"(r3) : "memory");
}
__device__ __forceinline__ void stsm_x1(uint32_t addr, uint32_t r0) {
  asm volatile("stmatrix.sync.aligned.m8n8.x1.shared.b16 [%0], {%1};\n" ::"r"(addr), "r"(r0) : "memory");
}
__device__ __forceinline__ void stsm_x4_t(uint32_t addr, uint32_t r0, uint32_t r1, uint32_t r2, uint32_t r3) {
  asm volatile("stmatrix.sync.aligned.m8n8.x4.trans.shared.b16 [%0], {%1,%2,%3,%4};\n" ::"r"(addr), "r"(r0), "r"(r1), "r"(r2), "r"(r3) : "memory");
}
__device__ __forceinline__ void stsm_x2_t(uint32_t addr, uint32_t r0, uint32_t r1) {
  asm volatile("stmatrix.sync.aligned.m8n8.x2.trans.shared.b16 [%0], {%1,%2};\n" ::"r"(addr), "r"(r0), "r"(r1) : "memory");
}
__device__ __forceinline__ void ldsm_x4_t(uint32_t addr, uint32_t& r0, uint32_t& r1, uint32_t& r2, uint32_t& r3) {
  asm volatile("ldmatrix.sync.aligned.m8n8.x4.trans.shared.b16 {%0,%1,%2,%3}, [%4];\n" : "=r"(r0), "=r"(r1), "=r"(r2), "=r"(r3) : "r"(addr) : "memory");
}
__device__ __forceinline__ void ldsm_x4(uint32_t addr, uint32_t* r) {
  asm volatile("ldmatrix.sync.aligned.m8n8.x4.shared.b16 {%0,%1,%2,%3}, [%4];\n" : "=r"(r[0]), "=r"(r[1]), "=r"(r[2]), "=r"(r[3]) : "r"(addr) : "memory");
}
__device__ __forceinline__ void stsm_x1_t(uint32_t addr, uint32_t r0) {
  asm volatile("stmatrix.sync.aligned.m8n8.x1.trans.shared.b16 [%0], {%1};\n" ::"r"(addr), "r"(r0) : "memory");
}
__device__ __forceinline__ int lds(uint32_t addr) {
  int v;
  asm volatile("ld.shared.u32 %0, [%1];\n" : "=r"(v) : "r"(addr) : "memory");
  return v;
}
__device__ __forceinline__ void mbar_init(uint32_t bar, int count) {
  asm volatile("mbarrier.init.shared::cta.b64 [%0], %1;\n" ::"r"(bar), "r"(count) : "memory");
}
__device__ __forceinline__ void mbar_expect_tx(uint32_t bar, int bytes) {
  asm volatile("mbarrier.arrive.expect_tx.shared::cta.b64 _, [%0], %1;\n" ::"r"(bar), "r"(bytes) : "memory");
}
__device__ __forceinline__ void mbar_wait(uint32_t bar, uint32_t parity) {
  asm volatile(
      "{\n.reg .pred p;\n"
      "WAIT_%=:\n"
      "mbarrier.try_wait.parity.shared::cta.b64 p, [%0], %1;\n"
      "@p bra DONE_%=;\n"
      "bra WAIT_%=;\n"
      "DONE_%=:\n}\n" ::"r"(bar), "r"(parity) : "memory");
}
__device__ __forceinline__ void tma_load_2d(uint32_t dst, const CUtensorMap* tm, int c0, int c1, uint32_t bar) {
  asm volatile("cp.async.bulk.tensor.2d.shared::cluster.global.mbarrier::complete_tx::bytes [%0], [%1, {%3, %4}], [%2];\n" ::"r"(dst),
               "l"(tm), "r"(bar), "r"(c0), "r"(c1) : "memory");
}
__device__ __forceinline__ void tma_load_3d(uint32_t dst, const CUtensorMap* tm, int c1, uint32_t bar) {
  asm volatile("cp.async.bulk.tensor.3d.shared::cluster.global.mbarrier::complete_tx::bytes [%0], [%1, {0, %3, 0}], [%2];\n" ::"r"(dst),
               "l"(tm), "r"(bar), "r"(c1) : "memory");
}
__device__ __forceinline__ bool elect_one() {
  uint32_t p;
  asm volatile("{\n.reg .pred p;\nelect.sync _|p, 0xffffffff;\nselp.u32 %0, 1, 0, p;\n}\n" : "=r"(p));
  return p;
}
__device__ __forceinline__ void tma_store_2d(const CUtensorMap* tm, uint32_t src, int c0, int c1) {
  asm volatile("cp.async.bulk.tensor.2d.global.shared::cta.bulk_group [%0, {%2, %3}], [%1];\n" ::"l"(tm), "r"(src), "r"(c0), "r"(c1) : "memory");
}

template <int N, int FIRST, int S0 = 0, int S1 = 8>
__device__ __forceinline__ void proj(float (&acc)[52], const uint32_t (&w)[32], uint64_t de) {
  wg_fence();
#pragma unroll
  for (int s = S0; s < S1; s++) {
    uint64_t db = de + (uint64_t)(((s >> 2) * N * 128 + (s & 3) * 32) >> 4);
    if (s == 0) mma_rs<N, FIRST>(acc, w[0], w[1], w[2], w[3], db);
    else mma_rs<N, 1>(acc, w[4 * s], w[4 * s + 1], w[4 * s + 2], w[4 * s + 3], db);
  }
  wg_commit();
}
__device__ __forceinline__ void issue_pv(float (&a)[52], const uint32_t (&vf)[28], uint64_t dp) {
  wg_fence();
#pragma unroll
  for (int s = 0; s < 6; s++) mma_rs<104, 1>(a, vf[4 * s], vf[4 * s + 1], vf[4 * s + 2], vf[4 * s + 3], dp + 16 * s);
  mma_rs<104, 1>(a, vf[24], vf[25], vf[26], vf[27], (dp + 16 * 6) & ~((uint64_t)0x3FFF << 16));
  wg_commit();
}
__device__ __forceinline__ void issue_s(float (&acc)[52], uint64_t dq, uint64_t dk) {
  wg_fence();
#pragma unroll
  for (int s = 0; s < 4; s++) {
    if (s == 0) mma_ss<false>(acc, dq, dk);
    else mma_ss<true>(acc, dq + 2 * s, dk + 2 * s);
  }
  wg_commit();
}

__device__ __forceinline__ void sched_barrier() { asm volatile("pmevent 1;\n" ::: "memory"); }
#define PINR(x) asm volatile("" : "+r"(x)::"memory")
#define PIN(x) asm volatile("" : "+f"(x)::"memory")

constexpr float kC = 0.125f * 1.4426950408889634f;

__device__ __forceinline__ bool out_of_range(float t) { return !(t >= 0x1p-30f && t <= 0x1p30f); }
__device__ __forceinline__ uint32_t mul_bf16x2(uint32_t a, uint32_t b) {
  uint32_t r;
  asm("mul.rn.bf16x2 %0, %1, %2;\n" : "=r"(r) : "r"(a), "r"(b));
  return r;
}
__device__ __forceinline__ uint32_t add_bf16x2(uint32_t a, uint32_t b) {
  uint32_t r;
  asm("add.rn.bf16x2 %0, %1, %2;\n" : "=r"(r) : "r"(a), "r"(b));
  return r;
}
__device__ __forceinline__ uint32_t quad_bcast(uint32_t v, uint32_t code) {
  uint32_t r;
  asm volatile("shfl.sync.idx.b32 %0, %1, %2, 0x31f, 0xffffffff;\n" : "=r"(r) : "r"(v), "r"(code));
  return r;
}
__device__ __forceinline__ float quad_sum(float t) {
  t += __shfl_xor_sync(0xffffffffu, t, 1);
  t += __shfl_xor_sync(0xffffffffu, t, 2);
  return t;
}
struct Q3 { float t, s1, s2, s3; };
__device__ __forceinline__ Q3 q3_start(float t) {
  Q3 q;
  q.t = t;
  q.s1 = __shfl_xor_sync(0xffffffffu, t, 1);
  q.s2 = __shfl_xor_sync(0xffffffffu, t, 2);
  q.s3 = __shfl_xor_sync(0xffffffffu, t, 3);
  return q;
}
__device__ __forceinline__ float q3_end(const Q3& q) { return (q.t + q.s1) + (q.s2 + q.s3); }
template <int O, int J0, int J1>
__device__ __forceinline__ void part_exp(const float (&s)[52], uint32_t (&p)[13], bool tail_invalid, float& t0, float& t1) {
#pragma unroll
  for (int j = J0; j < J1; j++) {
    const int jj = (j + 12) % 13;
    float x = ex2(s[4 * jj + O]), y = ex2(s[4 * jj + O + 1]);
    if (jj == 12 && tail_invalid) { x = 0.f; y = 0.f; }
    p[jj] = pack_bf16(x, y);
    if (j == 0) { t0 = x; t1 = y; } else { t0 += x; t0 += y; }
  }
}
template <int O>
__device__ __forceinline__ float set_max(const float (&s)[52], bool tail_invalid) {
  float m = fmaxf(s[O], s[O + 1]);
#pragma unroll
  for (int j = 1; j < 12; j++) m = fmaxf(m, fmaxf(s[4 * j + O], s[4 * j + O + 1]));
  if (!tail_invalid) m = fmaxf(m, fmaxf(s[48 + O], s[49 + O]));
  m = fmaxf(m, __shfl_xor_sync(0xffffffffu, m, 1));
  return fmaxf(m, __shfl_xor_sync(0xffffffffu, m, 2));
}
template <int O>
__device__ __forceinline__ float set_exact(const float (&s)[52], uint32_t (&p)[13], bool tail_invalid, float m) {
  float t0, t1;
#pragma unroll
  for (int j = 0; j < 13; j++) {
    const int jj = (j + 12) % 13;
    float x = ex2(s[4 * jj + O] - m), y = ex2(s[4 * jj + O + 1] - m);
    if (jj == 12 && tail_invalid) { x = 0.f; y = 0.f; }
    p[jj] = pack_bf16(x, y);
    if (j == 0) { t0 = x; t1 = y; } else { t0 += x; t1 += y; }
  }
  return quad_sum(t0 + t1);
}
__device__ __forceinline__ uint32_t inv2(float t) { const float iv = rcp(t); return pack_bf16(iv, iv); }
template <int C>
__device__ __forceinline__ void part_store(const uint32_t (&p)[13], uint32_t iv, uint32_t paddr) {
  if (C < 3) stsm_x4(paddr + C * 512, mul_bf16x2(p[4 * C], iv), mul_bf16x2(p[4 * C + 1], iv), mul_bf16x2(p[4 * C + 2], iv), mul_bf16x2(p[4 * C + 3], iv));
  else stsm_x1(paddr + 1536, mul_bf16x2(p[12], iv));
}
__device__ __forceinline__ void set_store(const uint32_t (&p)[13], float t, uint32_t paddr) {
  const uint32_t iv = inv2(t);
  part_store<0>(p, iv, paddr);
  part_store<1>(p, iv, paddr);
  part_store<2>(p, iv, paddr);
  part_store<3>(p, iv, paddr);
}

struct Params {
  const uint8_t* w[4];
  uint8_t* out;
  unsigned* claim;
  short n_pairs, n_extra, n_open, streams;
};
struct Maps { CUtensorMap m[8]; };
template <int V> using IC = std::integral_constant<int, V>;
using I104 = std::integral_constant<int, 104>;
using I96 = std::integral_constant<int, 96>;

__global__ void __launch_bounds__(512, 1)
autoint_kernel(const __grid_constant__ Params prm, const __grid_constant__ Maps tm) {
  extern __shared__ __align__(1024) uint8_t smem[];
  const uint32_t sbase = smem_u32(smem);
  const int tid = threadIdx.x;
  const uint32_t bar_full = sbase + kBarOff;
  const uint32_t bar_w = sbase + kBarOff + 64;
  const int cta = blockIdx.x, stream = cta >> 1, head = cta & 1;
  if (tid >= 256 && tid < 448) {
    if ((tid & 31) == 0) {
      const int k = (tid >> 5) - 8, m = (0x402153 >> (4 * (5 - k))) & 15;
      const uint32_t bar = m == 5 ? bar_full : bar_w + 8 * m;
      const uint32_t dst = sbase + (m == 0 ? kPOff : m == 1 ? kWkOff : m < 4 ? (m + 1) * kEStage : (m - 4) * kEHalf);
      const int c0 = m == 3 ? head * 64 : m == 5 ? 64 : 0, c1 = m < 3 ? head * 128 : m == 3 ? 0 : stream * 2 * kF;
      mbar_init(bar, 1);
      asm volatile("fence.mbarrier_init.release.cluster;\n" ::: "memory");
      fence_async();
      const long long c = clock64();
      while (clock64() - c < k * 60) {}
      mbar_expect_tx(bar, m < 4 ? 16384 : kEHalf);
      tma_load_2d(dst, &tm.m[3 + min(m, 4)], c0, c1, bar);
    }
  } else if (tid == 448) {
    for (int s = 1; s < kStages; s++) mbar_init(bar_full + 8 * s, 1);
    asm volatile("fence.mbarrier_init.release.cluster;\n" ::: "memory");
    asm volatile("st.shared.v2.u32 [%0], {%1,%1};\n" ::"r"(sbase + kZeroOff), "r"(0) : "memory");
    fence_async();
  } else if (tid < 192) {
    if (tid < 96 && (tid & 31) == 0) asm volatile("prefetch.tensormap [%0];\n" ::"l"(&tm.m[tid >> 5]) : "memory");
  } else if (tid >= 224) {
    if (tid < 250) asm volatile("st.shared.v4.u32 [%0], {%1,%1,%1,%1};\nst.shared.v4.u32 [%0 + 16], {%1,%1,%1,%1};\n"
                                ::"r"(sbase + kPOff + 12 * kPGrp + ((tid - 224) >> 1) * 128 + 64 + (tid & 1) * 32), "r"(0) : "memory");
  } else if (tid < 200) {
    asm volatile("prefetch.global.L2 [%0];\n" ::"l"(prm.w[(cta >> 5) & 3] + (cta & 31) * 1024 + (tid & 7) * 128) : "memory");
  }
  const int wg = __shfl_sync(0xffffffffu, tid >> 7, 0);
  __syncthreads();
  sched_barrier();
  const int n_pairs = prm.n_pairs, n_open = prm.n_open, streams = prm.streams;
  const int n_static = 2 * (n_pairs + (stream < prm.n_extra));
  const int n_tiles = n_static + (n_open > 0);
  auto row_of = [&](int i) {
    return i < n_static ? (((i >> 1) * streams + stream) * 2 + (i & 1)) * kF : lds(sbase + kCntOff + 4);
  };
  auto load_e = [&](int i, int st, int row) {
    mbar_expect_tx(bar_full + 8 * st, (i & 1) ? 2 * 96 * 128 : 2 * 104 * 128);
    tma_load_3d(sbase + st * kEStage, &tm.m[i & 1], row + (i & 1) * 4, bar_full + 8 * st);
  };
  auto next_row = [&](int i, int row) { return row + ((i & 1) ? (2 * streams - 1) * kF : kF); };
  auto read_count = [&]() { return __shfl_sync(0xffffffffu, lds(sbase + kCntOff), 0); };

#define ROLE_IDS()                                                                                     \
  int rtid;                                                                                            \
  asm volatile("mov.u32 %0, %tid.x;\n" : "=r"(rtid));                                                  \
  const int lane = rtid & 31;                                                                          \
  [[maybe_unused]] const int warp = __shfl_sync(0xffffffffu, (rtid >> 5) & 3, 0);                      \
  [[maybe_unused]] const uint32_t chunk = ((rtid >> 4) & 6) + ((lane >> 3) & 1);                       \
  [[maybe_unused]] const uint32_t t_off = ((lane >> 4) * 8 + (lane & 7)) * 128 + ((chunk ^ (lane & 7)) << 4)
  auto load_frags = [&](uint32_t (&w)[32], int m, uint32_t addr) {
    mbar_wait(bar_w + 8 * m, 0);
#pragma unroll
    for (int s = 0; s < 8; s++) ldsm_x4_t(addr + s * 2048, w[4 * s], w[4 * s + 1], w[4 * s + 2], w[4 * s + 3]);
  };
  const uint64_t dE0 = desc_sw128(sbase);
  auto finish = [&](int n_items) {
    int rtid;
    asm volatile("mov.u32 %0, %tid.x;\n" : "=r"(rtid));
    uint8_t* dst = prm.out + (size_t)row_of(n_items - 1) * (kD * 2) + head * 128;
    bar_sync(BAR_W, 512);
#pragma unroll
    for (int k = 0; k < 2; k++) {
      const int c = rtid + 512 * k, r = c >> 3;
      if (c < 8 * kF) {
        uint4 v;
        asm volatile("ld.shared.v4.u32 {%0,%1,%2,%3}, [%4];\n" : "=r"(v.x), "=r"(v.y), "=r"(v.z), "=r"(v.w)
                     : "r"(sbase + kOOff + r * 128 + (((c ^ r) & 7) << 4)) : "memory");
        *(uint4*)(dst + r * (kD * 2) + (c & 7) * 16) = v;
      }
    }
  };

  if (wg == 0) {
    asm volatile("setmaxnreg.inc.sync.aligned.u32 144;\n");
    ROLE_IDS();
    uint32_t wQ[32], wK[32];
    float acc[52];
    load_frags(wQ, 0, sbase + kPOff + t_off);
#pragma unroll
    for (int i = 0; i < 32; i++) wQ[i] = pack_bf16(__uint_as_float(wQ[i] << 16) * kC, __uint_as_float(wQ[i] & 0xffff0000u) * kC);
    int n_items = n_static;
    const uint32_t k_addr = sbase + kKOff + t_off, q_addr = sbase + kQOff + t_off;
    uint32_t pk[26];
    uint32_t e_off = 0, e_bar = bar_full, e_ph = 0;
    auto pack = [&](auto NC) {
      constexpr int N = decltype(NC)::value;
      wg_wait<0>();
      fence_acc<N>(acc);
#pragma unroll
      for (int i = 0; i < N / 4; i++) pk[i] = pack_bf16(acc[2 * i], acc[2 * i + 1]);
    };
    const bool server = warp == kStore;
    auto serve = [&](int it, int row) {
      bar_sync(BAR_O, 160);
      if (elect_one()) {
        fence_async();
        tma_store_2d(&tm.m[2], sbase + kOOff, head * 64, row);
        asm volatile("cp.async.bulk.commit_group;\n" ::: "memory");
      }
    };
    auto release_o = [&]() {
      asm volatile("cp.async.bulk.wait_group.read 0;\n" ::: "memory");
      __syncwarp();
      bar_arrive(BAR_OF, 160);
    };
    int st_row = 2 * stream * kF;
    auto publish = [&](int it) {
      const int n = it >= 2 ? 384 : 256;
      fence_async();
      bar_arrive(BAR_X, n);
      if (it < 2) bar_arrive(BAR_X + 1, 256);
    };
    auto item = [&](auto NC, auto FC, int it) {
      constexpr int N = decltype(NC)::value;
      constexpr bool first = decltype(FC)::value;
      constexpr int kPre = first ? 4 : 8;
      const uint64_t dE = dE0 + e_off;
      auto store_q = [&](int j0, int j1) {
#pragma unroll
        for (int j = j0; j < j1; j += 2) {
          if (j < 12) stsm_x4_t(q_addr + j * 1024, pk[2 * j], pk[2 * j + 1], pk[2 * j + 2], pk[2 * j + 3]);
          else if (N == 104) stsm_x2_t(q_addr + 12 * 1024, pk[24], pk[25]);
        }
      };
      if (first) {
        mbar_wait(bar_w + 32, 0);
        proj<N, 0, 0, 4>(acc, wQ, dE);
        bar_arrive(BAR_T1, 256);
        load_frags(wK, 1, q_addr + (kWkOff - kQOff));
        mbar_wait(bar_full, 0);
        proj<N, 0, 4, 8>(acc, wQ, dE);
        bar_arrive(BAR_S1, 256);
      } else {
        if (it >= 3) bar_sync(BAR_T1, 256);
        proj<N, 0>(acc, wQ, dE);
        if (N == 104 || it > 1) publish(it - 1);
        if (server && it >= 4) release_o();
      }
      pack(NC);
#pragma unroll
      for (int i = 0; i < N / 4; i++) asm volatile("" : "+r"(pk[i])::"memory");
      sched_barrier();
      if (!first) bar_sync(BAR_QE, 256);
      store_q(0, kPre);
      if (!first) bar_sync(BAR_SP + 1, 256);
      proj<N, 2>(acc, wK, dE);
      if (!first && (N == 104 || it > 1)) bar_arrive(BAR_S2, 256);
      if (first) bar_arrive(BAR_O, 256);
      store_q(kPre, 8);
      e_off += kEStage >> 4;
      e_bar += 8;
      if (e_off == kStages * (kEStage >> 4)) { e_off = 0; e_bar = bar_full; e_ph ^= 1; }
      if (!first) {
        if (it + 1 < n_tiles) mbar_wait(e_bar, e_ph);
        bar_sync(BAR_QE + 1, 256);
      }
      store_q(8, 14);
      if (!first && it >= 3) {
        if (server) serve(it - 3, st_row);
        st_row = next_row(it - 3, st_row);
      }
      if (N == 96 && it + 1 == n_static) n_items = read_count();
      pack(NC);
#pragma unroll
      for (int j = 0; j < 12; j += 2) stsm_x4_t(k_addr + j * 1024, pk[2 * j], pk[2 * j + 1], pk[2 * j + 2], pk[2 * j + 3]);
      if (N == 104) stsm_x2_t(k_addr + 12 * 1024, pk[24], pk[25]);
      if (!first && (N == 104 || it > 1)) bar_arrive(BAR_X + 1, 256);
      if (first) {
        fence_async();
        bar_arrive(BAR_X, 256);
        mbar_wait(bar_full + 8, 0);
        bar_sync(BAR_SP, 256);
        bar_arrive(BAR_X + 1, 256);
      }
    };
    item(I104{}, std::true_type{}, 0);
    for (int it = 1;; it += 2) {
      item(I96{}, std::false_type{}, it);
      if (it + 1 == n_items) break;
      item(I104{}, std::false_type{}, it + 1);
      if (it + 2 == n_items) break;
    }
    publish(n_items - 1);
    if (server) {
      for (int it = n_items - 3; it < n_items - 1; it++) {
        release_o();
        serve(it, st_row);
        st_row = next_row(it, st_row);
      }
      release_o();
    }
    finish(n_items);
  } else if (wg == 1) {
    asm volatile("setmaxnreg.inc.sync.aligned.u32 176;\n");
    ROLE_IDS();
    uint32_t wV[32], wR[32];
    float acc[52];
    uint32_t vf[28], pl[2];
    asm volatile("ld.volatile.shared.v2.u32 {%0, %1}, [%2];\n" : "=r"(vf[26]), "=r"(vf[27]) : "r"(sbase + kZeroOff) : "memory");
    load_frags(wV, 2, sbase + 3 * kEStage + t_off);
    int n_items = n_static;
    const uint32_t o_even = sbase + kOOff + t_off;
    const uint32_t r4 = (lane & 7) + 4;
    const uint32_t o_odd = sbase + kOOff + ((lane >> 4) * 8 + r4) * 128 + ((chunk ^ (r4 & 7)) << 4) + vf[26];
    const uint32_t o_odd_last = sbase + kOOff + ((lane & 4) ? (r4 & 7) : 96 + r4) * 128 + ((chunk ^ (r4 & 7)) << 4) + vf[26];
    const uint64_t dP = desc_p(sbase + kPOff);
    uint32_t e_off = 0;
    auto store_o = [&](int par, int it, int j0 = 0, int j1 = 14) {
      const uint32_t a = par ? o_odd : o_even;
      if (j0 == 0 && it >= 1) bar_sync(BAR_OF, 160);
#pragma unroll
      for (int j = j0; j < j1; j += 2) {
        if (j < 12) stsm_x4_t(a + j * 1024, vf[2 * j], vf[2 * j + 1], vf[2 * j + 2], vf[2 * j + 3]);
        else stsm_x2_t(par ? o_odd_last : o_even + 12 * 1024, pl[0], pl[1]);
      }
    };
    auto item = [&](auto NC, auto FC, int it) {
      constexpr int N = decltype(NC)::value, par = N == 96;
      constexpr bool first = decltype(FC)::value;
      const uint64_t dE = dE0 + e_off;
      if (first) {
        mbar_wait(bar_w + 32, 0);
        bar_sync(BAR_T1, 256);
        proj<N, 0, 0, 4>(acc, wV, dE);
        mbar_wait(bar_full, 0);
        bar_sync(BAR_S1, 256);
        proj<N, 0, 4, 8>(acc, wV, dE);
        load_frags(wR, 3, o_even + (4 * kEStage - kOOff));
        bar_arrive(BAR_W, 160);
      } else {
#pragma unroll
        for (int i = 0; i < 24; i++) asm volatile("" : "+r"(vf[i])::"memory");
        asm volatile("" : "+r"(pl[0]), "+r"(pl[1])::"memory");
        sched_barrier();
        if (it + 1 < n_items) bar_sync(BAR_SP, 256);
        proj<N, 2>(acc, wV, dE);
        if (it + 1 < n_items) bar_arrive(BAR_S1, 256);
        store_o(par ^ 1, it - 1, 0, 4);
        bar_sync(BAR_PF + par, 384);
        fence_async();
        if (par && it + 3 == n_static) n_items = read_count();
        store_o(par ^ 1, it - 1, 4, 14);
        bar_arrive(BAR_O, 160);
      }
      wg_wait<0>();
      fence_acc<N>(acc);
#pragma unroll
      for (int i = 0; i < N / 4; i++) {
        if (!first) asm("cvt.rn.bf16x2.f32 %0, %1, %2;\n" : "+r"(vf[i]) : "f"(acc[2 * i + 1]), "f"(acc[2 * i]));
        else vf[i] = pack_bf16(acc[2 * i], acc[2 * i + 1]);
      }
      if (first) bar_sync(BAR_O, 256);
      else {
#pragma unroll
        for (int i = 0; i < N / 4; i++) asm volatile("" : "+r"(vf[i])::"memory");
        sched_barrier();
        if (it + 2 < n_items) bar_sync(BAR_S2, 256);
      }
      proj<N, 2>(acc, wR, dE);
      if (first) {
        bar_sync(BAR_PF + par, 384);
        fence_async();
        bar_sync(BAR_SP, 256);
        bar_sync(BAR_S2, 256);
      }
      issue_pv(acc, vf, dP + (uint64_t)((par * kPBuf) >> 4));
      if (it + 3 < n_items) bar_arrive(BAR_T1, 256);
      e_off = e_off == (kStages - 1) * (kEStage >> 4) ? 0 : e_off + (kEStage >> 4);
      wg_wait<0>();
      if (it + 2 < n_items) bar_arrive(BAR_X, 384);
      sched_barrier();
      fence_acc(acc);
#pragma unroll
      for (int i = 0; i < 24; i++) asm("cvt.rn.relu.bf16x2.f32 %0, %1, %2;\n" : "+r"(vf[i]) : "f"(acc[2 * i + 1]), "f"(acc[2 * i]));
      pl[0] = pack_bf16_relu(acc[48], acc[49]);
      pl[1] = pack_bf16_relu(acc[50], acc[51]);
    };
    item(I104{}, std::true_type{}, 0);
    for (int it = 1;; it += 2) {
      item(I96{}, std::false_type{}, it);
      if (it + 1 == n_items) break;
      item(I104{}, std::false_type{}, it + 1);
      if (it + 2 == n_items) break;
    }
    store_o((n_items - 1) & 1, n_items - 1);
    finish(n_items);
  } else {
    if (wg == 2) {
      asm volatile("setmaxnreg.dec.sync.aligned.u32 96;\n");
      ROLE_IDS();
      const uint64_t dK = desc_sw128(sbase + kKOff);
      float acc[52];
      const uint64_t dQ = desc_sw128(sbase + kQOff);
      uint32_t pa = sbase + kPOff + 2 * warp * kPGrp + lane * 16;
      int tail = (lane >> 1) & 1;
      if (rtid == 256) {
        mbar_wait(bar_w, 0);
        load_e(1, 1, row_of(1));
        mbar_wait(bar_full, 0);
        load_e(2, 2, row_of(2));
      }
      if (rtid == 320) {
        const int m = max(n_open, 1), x = stream % m;
        asm volatile("st.shared.v4.u32 [%0], {%1,%2,%3,%4};\n" ::"r"(sbase + kCntOff), "r"(n_static), "r"((2 * n_pairs * streams + x) * kF),
                     "r"(2 * x + head), "r"((streams - 1 - x) / m) : "memory");
      }
      if (warp == kServe) bar_sync(BAR_W, 160);
      __syncwarp();
      int n_items = n_static;
      int ld_row = (2 * (streams + stream) + 1) * kF, ld_st = 3;
      uint32_t ticket = 1;
      for (int it = 0; it < n_items; it++) {
        bar_sync(BAR_X, it >= 2 ? 384 : 256);
        issue_s(acc, dQ, dK);
        bar_arrive(BAR_SP, 256);
        if (warp == kServe && it + 3 < n_tiles) {
          if (it + 3 == n_static) ld_row = __shfl_sync(0xffffffffu, lds(sbase + kCntOff + 4), 0);
          if (elect_one()) load_e(it + 3, ld_st, ld_row);
        }
        ld_row = next_row(it + 3, ld_row);
        ld_st = ld_st == kStages - 1 ? 0 : ld_st + 1;
        if (it + 1 == n_static) n_items = read_count();
        wg_wait<0>();
        if (it + 1 < n_items) bar_arrive(BAR_QE, 256);
        if (ticket == 0) asm volatile("st.shared.u32 [%0], %1;\n" ::"r"(sbase + kCntOff), "r"(it + 5) : "memory");
        sched_barrier();
        fence_acc(acc);
        uint32_t p0[13], p1[13];
        float t0, t1, u0, u1;
        part_exp<0, 0, 13>(acc, p0, tail, t0, u0);
        part_exp<2, 0, 2>(acc, p1, tail, t1, u1);
        t0 += u0;
        u0 = __shfl_xor_sync(0xffffffffu, t0, 1);
        PIN(t1); PIN(u1);
        sched_barrier();
        part_exp<2, 2, 6>(acc, p1, tail, t1, u1);
        PIN(t1); PIN(u1);
        sched_barrier();
        t0 += u0;
        u0 = __shfl_xor_sync(0xffffffffu, t0, 2);
        sched_barrier();
        part_exp<2, 6, 10>(acc, p1, tail, t1, u1);
        PIN(t1); PIN(u1);
        sched_barrier();
        t0 += u0;
        const uint32_t i0 = inv2(t0);
        part_store<0>(p0, i0, pa);
        part_exp<2, 10, 13>(acc, p1, tail, t1, u1);
        const Q3 q1 = q3_start(t1 + u1);
        sched_barrier();
        part_store<1>(p0, i0, pa);
        part_store<2>(p0, i0, pa);
        part_store<3>(p0, i0, pa);
        sched_barrier();
        t1 = q3_end(q1);
        if (__builtin_expect(__any_sync(0xffffffffu, out_of_range(t0) || out_of_range(t1)), 0)) {
          set_store(p0, set_exact<0>(acc, p0, tail, set_max<0>(acc, tail)), pa);
          t1 = set_exact<2>(acc, p1, tail, set_max<2>(acc, tail));
        }
        set_store(p1, t1, pa + kPGrp);
        bar_arrive(BAR_PF + (it & 1), 384);
        ticket = 1;
        if (it + 5 == n_static && n_open > 0 && warp == kClaim) {
          if (elect_one())
            asm volatile("atom.global.inc.u32 %0, [%1], %2;\n" : "=r"(ticket) : "l"(prm.claim + lds(sbase + kCntOff + 8)), "r"(lds(sbase + kCntOff + 12)) : "memory");
        }
        pa += (it & 1) ? -kPBuf : kPBuf;
        tail ^= 1;
      }
      finish(n_items);
    } else {
      asm volatile("setmaxnreg.dec.sync.aligned.u32 96;\n");
      ROLE_IDS();
      const uint64_t dQ = desc_sw128(sbase + kQOff + 8192);
      uint32_t k_addr = sbase + kKOff + ((lane & 8) ? 12 : 8 + warp) * 1024 + (lane & 7) * 128 + (((lane >> 4) ^ (lane & 7)) << 4);
      const uint32_t pa = sbase + kPOff + (8 + (lane >> 3)) * kPGrp + 2 * warp * 128 + (lane & 7) * 16 + kPBuf;
      const uint32_t trash = sbase + kTrashOff + lane * 16;
      const uint32_t pd = sbase + kPOff + (lane < 24 ? 12 * kPGrp + (lane < 16 ? 2 * warp + (lane >> 3) : 8 + warp) * 128 : (8 + warp) * kPGrp + 12 * 128) + (lane & 7) * 16;
      uint32_t pd0 = lane >= 24 || (lane & 4) ? pd + kPBuf : trash;
      const uint32_t pdx = pd0 ^ (lane >= 24 || !(lane & 4) ? pd : trash);
      uint32_t sum_addr = sbase + kSumOff + lane * 16;
      asm volatile("xor.b32 %0, %0, %1;\n" : "+r"(sum_addr) : "r"(lds(sbase + kZeroOff)));
      const uint32_t d_code = ((warp & 1) << 4) | ((warp & 2) << 2);
      int n_items = n_static;
      uint32_t kf[16 + 4 * kRs];
      uint32_t k0_addr = sbase + kKOff + (2 * warp + ((lane >> 3) & 1)) * 1024 + (lane & 7) * 128 + (((lane >> 4) ^ (lane & 7)) << 4);
      asm volatile("xor.b32 %0, %0, %2;\nxor.b32 %1, %1, %2;\n" : "+r"(k_addr), "+r"(k0_addr) : "r"(lds(sbase + kZeroOff)));
      const uint64_t dK = desc_sw128(sbase + kKOff);
      auto load_k = [&](bool more, auto S0, auto S1) {
        constexpr int s0 = decltype(S0)::value, s1 = decltype(S1)::value;
        if (s0 == 0 && more) bar_sync(BAR_X + 1, 256);
#pragma unroll
        for (int s = s0; s < s1; s++) {
          uint32_t a = s < 4 ? k_addr : k0_addr;
          if (s & 3) asm volatile("xor.b32 %0, %1, %2;\n" : "=r"(a) : "r"(s < 4 ? k_addr : k0_addr), "r"((s & 3) << 5));
          ldsm_x4(a, kf + 4 * s);
        }
      };
      load_k(true, IC<0>{}, IC<4 + kRs>{});
      for (int it = 0; it < n_items; it++) {
        float t0[20], t1[20];
        if (it >= 2) bar_sync(BAR_S1, 256);
        wg_fence();
#pragma unroll
        for (int s = 0; s < 4; s++) {
          if (s) mma_rs40<true>(t1, kf + 4 * s, dQ + 2 * s); else mma_rs40<false>(t1, kf, dQ);
          if (s < kRs) { if (s) mma_rs40<true>(t0, kf + 16 + 4 * s, dQ + 2 * s); else mma_rs40<false>(t0, kf + 16, dQ); }
          else mma_ss40(t0, dK + 2 * s, dQ + 2 * s);
        }
        wg_commit();
        if (it + 1 < n_items) bar_arrive(BAR_SP + 1, 256);
        sched_barrier();
        pd0 ^= pdx;
        PINR(pd0);
        const uint32_t po = (it & 1) * kPBuf - kPBuf;
        if (it + 2 == n_static) n_items = read_count();
        sched_barrier();
        wg_wait<0>();
        if (it + 1 < n_items) bar_arrive(BAR_QE + 1, 256);
        sched_barrier();
        asm volatile("" : ACC20_OPS("+f", t0)::"memory");
        asm volatile("" : ACC20_OPS("+f", t1)::"memory");
        const bool b4 = sum_addr & 256, b3 = sum_addr & 128, b2 = sum_addr & 64;
        const bool tail = (sum_addr ^ (it << 5)) & 32, other = (sum_addr ^ (it << 8)) & 256;
        uint32_t pA[5], pB[5], pC[5], d0, d1, iv;
        for (int pass = 0;; pass++) {
          auto d_part = [&]() {
            float a0, a1;
            if (warp & 2) { if (warp & 1) { a0 = ex2(t1[14]); a1 = ex2(t1[15]); } else { a0 = ex2(t1[10]); a1 = ex2(t1[11]); } }
            else { if (warp & 1) { a0 = ex2(t1[6]); a1 = ex2(t1[7]); } else { a0 = ex2(t1[2]); a1 = ex2(t1[3]); } }
            d0 = pack_bf16(a0, a1);
            d1 = pack_bf16(ex2(t1[18]), ex2(t1[19]));
            if (other) d0 = 0;
            if (other || warp != 3) d1 = 0;
          };
          d_part();
          auto col = [&](int j) {
            pA[j] = pack_bf16(ex2(t0[4 * j]), ex2(t0[4 * j + 1]));
            pB[j] = pack_bf16(ex2(t0[4 * j + 2]), ex2(t0[4 * j + 3]));
            pC[j] = pack_bf16(ex2(t1[4 * j]), ex2(t1[4 * j + 1]));
            uint32_t z = add_bf16x2(add_bf16x2(pA[j], pB[j]), pC[j]);
            if (j == 4) z = add_bf16x2(z, d1);
            else if (warp == j) z = add_bf16x2(z, d0);
            return z;
          };
          const uint32_t z4 = col(4), z0 = col(0), z1 = col(1);
          const uint32_t s4 = __shfl_xor_sync(0xffffffffu, z4, 16);
          const uint32_t k0 = b4 ? z1 : z0, s0 = __shfl_xor_sync(0xffffffffu, b4 ? z0 : z1, 16);
          const uint32_t z2 = col(2), z3 = col(3);
          const uint32_t y0 = add_bf16x2(k0, s0), y2 = add_bf16x2(z4, s4);
          const uint32_t y1 = add_bf16x2(b4 ? z3 : z2, __shfl_xor_sync(0xffffffffu, b4 ? z2 : z3, 16));
          const uint32_t x1 = add_bf16x2(y2, __shfl_xor_sync(0xffffffffu, y2, 8));
          const uint32_t x0 = add_bf16x2(b3 ? y1 : y0, __shfl_xor_sync(0xffffffffu, b3 ? y0 : y1, 8));
          uint4 u;
          const uint32_t w = add_bf16x2(b2 ? x1 : x0, __shfl_xor_sync(0xffffffffu, b2 ? x0 : x1, 4));
          asm volatile("{\n.reg .u32 a;\nadd.u32 a, %0, %2;\nst.shared.u32 [a], %1;\n}\n" ::"r"(sum_addr), "r"(w), "r"(warp * 4) : "memory");
          bar_sync(BAR_D, 128);
          asm volatile("ld.shared.v4.u32 {%0,%1,%2,%3}, [%4];\n" : "=r"(u.x), "=r"(u.y), "=r"(u.z), "=r"(u.w) : "r"(sum_addr) : "memory");
          load_k(it + 1 < n_items && !pass, IC<0>{}, IC<4>{});
          u.x = add_bf16x2(u.x, u.y);
          u.z = add_bf16x2(u.z, u.w);
          const float lo = __uint_as_float(u.x << 16) + __uint_as_float(u.z << 16);
          const float hi = __uint_as_float(u.x & 0xffff0000u) + __uint_as_float(u.z & 0xffff0000u);
          iv = pack_bf16(rcp(lo), rcp(hi));
          if (__builtin_expect(!__any_sync(0xffffffffu, !(b2 && tail) && (out_of_range(lo) | out_of_range(hi))) || pass, 1)) break;
          float m[10];
          const uint32_t max_addr = sbase + kMaxOff + (((sum_addr + lds(sbase + kZeroOff)) >> 4) & 3) * 192;
#pragma unroll
          for (int k = 0; k < 10; k++) {
            const int i = 4 * (k >> 1) + (k & 1);
            m[k] = fmaxf(fmaxf(t0[i], t0[i + 2]), other ? t1[i] : fmaxf(t1[i], t1[i + 2]));
            m[k] = fmaxf(m[k], __shfl_xor_sync(0xffffffffu, m[k], 4));
            m[k] = fmaxf(m[k], __shfl_xor_sync(0xffffffffu, m[k], 8));
            m[k] = fmaxf(m[k], __shfl_xor_sync(0xffffffffu, m[k], 16));
            asm volatile("st.shared.f32 [%0], %1;\n" ::"r"(max_addr + k * 16 + warp * 4), "f"(m[k]) : "memory");
          }
          bar_sync(BAR_D, 128);
#pragma unroll
          for (int k = 0; k < 10; k++) {
            const int i = 4 * (k >> 1) + (k & 1);
            float4 v;
            asm volatile("ld.shared.v4.f32 {%0,%1,%2,%3}, [%4];\n" : "=f"(v.x), "=f"(v.y), "=f"(v.z), "=f"(v.w) : "r"(max_addr + k * 16) : "memory");
            const float mk = fmaxf(fmaxf(v.x, v.y), fmaxf(v.z, v.w));
            t0[i] -= mk; t0[i + 2] -= mk; t1[i] -= mk; t1[i + 2] -= mk;
          }
        }
        const uint32_t i0 = quad_bcast(iv, 0), i1 = quad_bcast(iv, 16), i2 = quad_bcast(iv, 8), i3 = quad_bcast(iv, 24);
        const uint32_t i4 = quad_bcast(iv, 4), id = quad_bcast(iv, d_code);
        stsm_x4_t(pa + po, mul_bf16x2(pA[0], i0), mul_bf16x2(pA[1], i1), mul_bf16x2(pA[2], i2), mul_bf16x2(pA[3], i3));
        stsm_x4_t(pa + po + 128, mul_bf16x2(pB[0], i0), mul_bf16x2(pB[1], i1), mul_bf16x2(pB[2], i2), mul_bf16x2(pB[3], i3));
        stsm_x4_t(pa + (po + (8 - warp) * 128), mul_bf16x2(pC[0], i0), mul_bf16x2(pC[1], i1), mul_bf16x2(pC[2], i2), mul_bf16x2(pC[3], i3));
        stsm_x4_t(pd0, mul_bf16x2(pA[4], i4), mul_bf16x2(pB[4], i4), mul_bf16x2(pC[4], i4), mul_bf16x2(d0, id));
        if (warp == 3) stsm_x1_t(pd0 + 6 * 128, mul_bf16x2(d1, i4));
        bar_arrive(BAR_PF + (it & 1), 384);
        load_k(false, IC<4>{}, IC<4 + kRs>{});
      }
      finish(n_items);
    }
  }
}

typedef CUresult (*EncodeFn)(CUtensorMap*, CUtensorMapDataType, cuuint32_t, void*, const cuuint64_t*, const cuuint64_t*,
                             const cuuint32_t*, const cuuint32_t*, CUtensorMapInterleave, CUtensorMapSwizzle,
                             CUtensorMapL2promotion, CUtensorMapFloatOOBfill);

}

extern "C" void kernel_launch(void* const* d_in, const int* in_sizes, int n_in, void* d_out, int out_size) {
  static EncodeFn encode = nullptr;
  static int num_sms = 0;
  static unsigned* claim = nullptr;
  if (!encode) {
    void* fn = nullptr;
    cudaDriverEntryPointQueryResult qres;
    cudaGetDriverEntryPoint("cuTensorMapEncodeTiled", &fn, cudaEnableDefault, &qres);
    encode = (EncodeFn)fn;
    int dev = 0;
    cudaGetDevice(&dev);
    cudaDeviceGetAttribute(&num_sms, cudaDevAttrMultiProcessorCount, dev);
    cudaGetSymbolAddress((void**)&claim, g_claim);
    cudaFuncSetAttribute(autoint_kernel, cudaFuncAttributeMaxDynamicSharedMemorySize, kSmemBytes);
  }
  auto make = [&](void* p, uint64_t cols, uint64_t rows, uint32_t box_rows, CUtensorMapL2promotion promo) {
    CUtensorMap tm;
    cuuint64_t dims[2] = {cols, rows};
    cuuint64_t strides[1] = {cols * 2};
    cuuint32_t box[2] = {64, box_rows};
    cuuint32_t estr[2] = {1, 1};
    encode(&tm, CU_TENSOR_MAP_DATA_TYPE_BFLOAT16, 2, p, dims, strides, box, estr, CU_TENSOR_MAP_INTERLEAVE_NONE,
           CU_TENSOR_MAP_SWIZZLE_128B, promo, CU_TENSOR_MAP_FLOAT_OOB_FILL_NONE);
    return tm;
  };
  Maps tm;
  for (int i = 0; i < 2; i++) {
    cuuint64_t dims[3] = {64, (cuuint64_t)kB * kF, 2};
    cuuint64_t strides[2] = {kD * 2, 128};
    cuuint32_t box[3] = {64, i ? 96u : 104u, 2};
    cuuint32_t estr[3] = {1, 1, 1};
    encode(&tm.m[i], CU_TENSOR_MAP_DATA_TYPE_BFLOAT16, 3, d_in[0], dims, strides, box, estr, CU_TENSOR_MAP_INTERLEAVE_NONE,
           CU_TENSOR_MAP_SWIZZLE_128B, CU_TENSOR_MAP_L2_PROMOTION_L2_256B, CU_TENSOR_MAP_FLOAT_OOB_FILL_NONE);
  }
  tm.m[2] = make(d_out, kD, (uint64_t)kB * kF, kF, CU_TENSOR_MAP_L2_PROMOTION_NONE);
  for (int i = 0; i < 3; i++) tm.m[3 + i] = make(d_in[1 + i], 64, 256, 128, CU_TENSOR_MAP_L2_PROMOTION_L2_256B);
  tm.m[6] = make(d_in[4], 128, 128, 128, CU_TENSOR_MAP_L2_PROMOTION_L2_256B);
  tm.m[7] = make(d_in[0], kD, (uint64_t)kB * kF, 104, CU_TENSOR_MAP_L2_PROMOTION_L2_128B);
  const int grid = (num_sms < 2 ? 2 : num_sms > 256 ? 256 : num_sms) & ~1, streams = grid / 2;
  const int n_pairs = kB / 2 / streams, rem = kB / 2 - n_pairs * streams;
  const bool open = 2 * rem <= streams;
  Params prm;
  for (int i = 0; i < 4; i++) prm.w[i] = (const uint8_t*)d_in[1 + i];
  prm.out = (uint8_t*)d_out;
  prm.claim = claim;
  prm.n_pairs = (short)n_pairs;
  prm.n_extra = (short)(open ? 0 : rem);
  prm.n_open = (short)(open ? 2 * rem : 0);
  prm.streams = (short)streams;
  autoint_kernel<<<grid, 512, kSmemBytes>>>(prm, tm);
}
```

```cpp
#include <cuda_runtime.h>
#include <cuda_bf16.h>
#include <cuda.h>
#include <stdint.h>
#include <type_traits>

namespace {

constexpr int kB = 4096, kF = 100, kD = 128;
constexpr int kStages = 5;
constexpr int kServe = 1, kStore = 2, kClaim = 3;
constexpr int kRs = 2;
constexpr int kEHalf = 104 * 128;
constexpr int kEStage = 2 * kEHalf;
constexpr int kQOff = kStages * kEStage;
constexpr int kKOff = kQOff + 13312;
constexpr int kPOff = kKOff + 16384;
constexpr int kPGrp = 13 * 128;
constexpr int kPBuf = 13 * kPGrp;
constexpr int kWkOff = kPOff + 22528;
constexpr int kOOff = kPOff + 44032;
constexpr int kBarOff = kOOff + 13312;
constexpr int kTrashOff = kBarOff + 128;
constexpr int kSumOff = kTrashOff + 1920;
constexpr int kMaxOff = kSumOff + 1024;
constexpr int kZeroOff = kMaxOff + 768;
constexpr int kCntOff = kZeroOff + 16;
constexpr int kSmemBytes = kZeroOff + 128;
static_assert(kSumOff % 512 == 0 && kQOff % 1024 == 0 && kKOff % 1024 == 0 && kPOff % 1024 == 0 && kOOff % 1024 == 0 && kWkOff % 1024 == 0 &&
              2 * kPBuf <= 44032 && kWkOff >= kPOff + kPBuf && kWkOff + 16384 <= kOOff && kSmemBytes <= 232448, "smem layout");

enum {
  BAR_T1 = 1,
  BAR_X = 2,
  BAR_QE = 4,
  BAR_PF = 6,
  BAR_O = 8,
  BAR_S2 = 9,
  BAR_W = 10,
  BAR_SP = 11,
  BAR_OF = 13,
  BAR_D = 14,
  BAR_S1 = 15
};

__device__ unsigned g_claim[256];

__device__ __forceinline__ uint32_t smem_u32(const void* p) { return (uint32_t)__cvta_generic_to_shared(p); }

__device__ __forceinline__ void wg_fence() { asm volatile("wgmma.fence.sync.aligned;\n" ::: "memory"); }
__device__ __forceinline__ void wg_commit() { asm volatile("wgmma.commit_group.sync.aligned;\n" ::: "memory"); }
template <int N> __device__ __forceinline__ void wg_wait() { asm volatile("wgmma.wait_group.sync.aligned %0;\n" ::"n"(N) : "memory"); }
__device__ __forceinline__ void fence_async() { asm volatile("fence.proxy.async.shared::cta;\n" ::: "memory"); }
__device__ __forceinline__ void bar_sync(int id, int n) { asm volatile("bar.sync %0, %1;\n" ::"r"(id), "r"(n) : "memory"); }
__device__ __forceinline__ void bar_arrive(int id, int n) { asm volatile("bar.arrive %0, %1;\n" ::"r"(id), "r"(n) : "memory"); }

#define ACC48_REGS "%0,%1,%2,%3,%4,%5,%6,%7,%8,%9,%10,%11,%12,%13,%14,%15,%16,%17,%18,%19,%20,%21,%22,%23,%24,%25," \
                   "%26,%27,%28,%29,%30,%31,%32,%33,%34,%35,%36,%37,%38,%39,%40,%41,%42,%43,%44,%45,%46,%47"
#define ACC_REGS "{" ACC48_REGS ",%48,%49,%50,%51}"
#define ACC48_OPS(c, d)                                                                                      \
  c(d[0]), c(d[1]), c(d[2]), c(d[3]), c(d[4]), c(d[5]), c(d[6]), c(d[7]), c(d[8]), c(d[9]), c(d[10]),        \
  c(d[11]), c(d[12]), c(d[13]), c(d[14]), c(d[15]), c(d[16]), c(d[17]), c(d[18]), c(d[19]), c(d[20]),        \
  c(d[21]), c(d[22]), c(d[23]), c(d[24]), c(d[25]), c(d[26]), c(d[27]), c(d[28]), c(d[29]), c(d[30]),        \
  c(d[31]), c(d[32]), c(d[33]), c(d[34]), c(d[35]), c(d[36]), c(d[37]), c(d[38]), c(d[39]), c(d[40]),        \
  c(d[41]), c(d[42]), c(d[43]), c(d[44]), c(d[45]), c(d[46]), c(d[47])
#define ACC_OPS(c, d) ACC48_OPS(c, d), c(d[48]), c(d[49]), c(d[50]), c(d[51])

template <int N = 104>
__device__ __forceinline__ void fence_acc(float (&d)[52]) {
  if constexpr (N == 104) asm volatile("" : ACC_OPS("+f", d)::"memory");
  else asm volatile("" : ACC48_OPS("+f", d)::"memory");
}

template <int N, int ACC>
__device__ __forceinline__ void mma_rs(float (&d)[52], uint32_t a0, uint32_t a1, uint32_t a2, uint32_t a3, uint64_t db) {
  if constexpr (N == 104 && ACC) {
    asm volatile("wgmma.mma_async.sync.aligned.m64n104k16.f32.bf16.bf16 " ACC_REGS
                 ", {%52,%53,%54,%55}, %56, %57, 1, 1, 0;\n"
                 : ACC_OPS("+f", d)
                 : "r"(a0), "r"(a1), "r"(a2), "r"(a3), "l"(db), "n"(ACC & 1));
  } else if constexpr (N == 104) {
    asm volatile("wgmma.mma_async.sync.aligned.m64n104k16.f32.bf16.bf16 " ACC_REGS
                 ", {%52,%53,%54,%55}, %56, 0, 1, 1, 0;\n"
                 : ACC_OPS("=f", d)
                 : "r"(a0), "r"(a1), "r"(a2), "r"(a3), "l"(db));
  } else if constexpr (ACC) {
    asm volatile("wgmma.mma_async.sync.aligned.m64n96k16.f32.bf16.bf16 {" ACC48_REGS
                 "}, {%48,%49,%50,%51}, %52, %53, 1, 1, 0;\n"
                 : ACC48_OPS("+f", d)
                 : "r"(a0), "r"(a1), "r"(a2), "r"(a3), "l"(db), "n"(ACC & 1));
  } else {
    asm volatile("wgmma.mma_async.sync.aligned.m64n96k16.f32.bf16.bf16 {" ACC48_REGS
                 "}, {%48,%49,%50,%51}, %52, 0, 1, 1, 0;\n"
                 : ACC48_OPS("=f", d)
                 : "r"(a0), "r"(a1), "r"(a2), "r"(a3), "l"(db));
  }
}
template <bool ACC>
__device__ __forceinline__ void mma_ss(float (&d)[52], uint64_t da, uint64_t db) {
  if constexpr (ACC) {
    asm volatile("wgmma.mma_async.sync.aligned.m64n104k16.f32.bf16.bf16 " ACC_REGS ", %52, %53, 1, 1, 1, 0, 0;\n"
                 : ACC_OPS("+f", d)
                 : "l"(da), "l"(db));
  } else {
    asm volatile("wgmma.mma_async.sync.aligned.m64n104k16.f32.bf16.bf16 " ACC_REGS ", %52, %53, 0, 1, 1, 0, 0;\n"
                 : ACC_OPS("=f", d)
                 : "l"(da), "l"(db));
  }
}

#define ACC20_OPS(c, d)                                                                                      \
  c(d[0]), c(d[1]), c(d[2]), c(d[3]), c(d[4]), c(d[5]), c(d[6]), c(d[7]), c(d[8]), c(d[9]), c(d[10]),        \
  c(d[11]), c(d[12]), c(d[13]), c(d[14]), c(d[15]), c(d[16]), c(d[17]), c(d[18]), c(d[19])
#define ACC20_REGS "{%0,%1,%2,%3,%4,%5,%6,%7,%8,%9,%10,%11,%12,%13,%14,%15,%16,%17,%18,%19}"
template <bool ACC>
__device__ __forceinline__ void mma_rs40(float (&d)[20], const uint32_t* a, uint64_t db) {
  if constexpr (ACC) {
    asm volatile("wgmma.mma_async.sync.aligned.m64n40k16.f32.bf16.bf16 " ACC20_REGS ", {%20,%21,%22,%23}, %24, 1, 1, 1, 0;\n"
                 : ACC20_OPS("+f", d) : "r"(a[0]), "r"(a[1]), "r"(a[2]), "r"(a[3]), "l"(db));
  } else {
    asm volatile("wgmma.mma_async.sync.aligned.m64n40k16.f32.bf16.bf16 " ACC20_REGS ", {%20,%21,%22,%23}, %24, 0, 1, 1, 0;\n"
                 : ACC20_OPS("=f", d) : "r"(a[0]), "r"(a[1]), "r"(a[2]), "r"(a[3]), "l"(db));
  }
}

__device__ __forceinline__ void mma_ss40(float (&d)[20], uint64_t da, uint64_t db) {
  asm volatile("wgmma.mma_async.sync.aligned.m64n40k16.f32.bf16.bf16 " ACC20_REGS ", %20, %21, 1, 1, 1, 0, 0;\n" : ACC20_OPS("+f", d) : "l"(da), "l"(db));
}

__device__ __forceinline__ uint64_t desc_sw128(uint32_t saddr) {
  return (uint64_t)((saddr & 0x3FFFF) >> 4) | ((uint64_t)1 << 16) | ((uint64_t)(1024 >> 4) << 32) | ((uint64_t)1 << 62);
}
__device__ __forceinline__ uint64_t desc_p(uint32_t saddr) {
  return (uint64_t)((saddr & 0x3FFFF) >> 4) | ((uint64_t)(128 >> 4) << 16) | ((uint64_t)(kPGrp >> 4) << 32);
}

__device__ __forceinline__ uint32_t pack_bf16(float lo, float hi) {
  uint32_t r;
  asm("cvt.rn.bf16x2.f32 %0, %1, %2;\n" : "=r"(r) : "f"(hi), "f"(lo));
  return r;
}
__device__ __forceinline__ uint32_t pack_bf16_relu(float lo, float hi) {
  uint32_t r;
  asm("cvt.rn.relu.bf16x2.f32 %0, %1, %2;\n" : "=r"(r) : "f"(hi), "f"(lo));
  return r;
}
__device__ __forceinline__ float ex2(float x) {
  float y;
  asm("ex2.approx.ftz.f32 %0, %1;\n" : "=f"(y) : "f"(x));
  return y;
}
__device__ __forceinline__ float rcp(float x) {
  float y;
  asm("rcp.approx.ftz.f32 %0, %1;\n" : "=f"(y) : "f"(x));
  return y;
}
__device__ __forceinline__ void stsm_x4(uint32_t addr, uint32_t r0, uint32_t r1, uint32_t r2, uint32_t r3) {
  asm volatile("stmatrix.sync.aligned.m8n8.x4.shared.b16 [%0], {%1,%2,%3,%4};\n" ::"r"(addr), "r"(r0), "r"(r1), "r"(r2), "r"(r3) : "memory");
}
__device__ __forceinline__ void stsm_x1(uint32_t addr, uint32_t r0) {
  asm volatile("stmatrix.sync.aligned.m8n8.x1.shared.b16 [%0], {%1};\n" ::"r"(addr), "r"(r0) : "memory");
}
__device__ __forceinline__ void stsm_x4_t(uint32_t addr, uint32_t r0, uint32_t r1, uint32_t r2, uint32_t r3) {
  asm volatile("stmatrix.sync.aligned.m8n8.x4.trans.shared.b16 [%0], {%1,%2,%3,%4};\n" ::"r"(addr), "r"(r0), "r"(r1), "r"(r2), "r"(r3) : "memory");
}
__device__ __forceinline__ void stsm_x2_t(uint32_t addr, uint32_t r0, uint32_t r1) {
  asm volatile("stmatrix.sync.aligned.m8n8.x2.trans.shared.b16 [%0], {%1,%2};\n" ::"r"(addr), "r"(r0), "r"(r1) : "memory");
}
__device__ __forceinline__ void ldsm_x4_t(uint32_t addr, uint32_t& r0, uint32_t& r1, uint32_t& r2, uint32_t& r3) {
  asm volatile("ldmatrix.sync.aligned.m8n8.x4.trans.shared.b16 {%0,%1,%2,%3}, [%4];\n" : "=r"(r0), "=r"(r1), "=r"(r2), "=r"(r3) : "r"(addr) : "memory");
}
__device__ __forceinline__ void ldsm_x4(uint32_t addr, uint32_t* r) {
  asm volatile("ldmatrix.sync.aligned.m8n8.x4.shared.b16 {%0,%1,%2,%3}, [%4];\n" : "=r"(r[0]), "=r"(r[1]), "=r"(r[2]), "=r"(r[3]) : "r"(addr) : "memory");
}
__device__ __forceinline__ void stsm_x1_t(uint32_t addr, uint32_t r0) {
  asm volatile("stmatrix.sync.aligned.m8n8.x1.trans.shared.b16 [%0], {%1};\n" ::"r"(addr), "r"(r0) : "memory");
}
__device__ __forceinline__ int lds(uint32_t addr) {
  int v;
  asm volatile("ld.shared.u32 %0, [%1];\n" : "=r"(v) : "r"(addr) : "memory");
  return v;
}
__device__ __forceinline__ void mbar_init(uint32_t bar, int count) {
  asm volatile("mbarrier.init.shared::cta.b64 [%0], %1;\n" ::"r"(bar), "r"(count) : "memory");
}
__device__ __forceinline__ void mbar_expect_tx(uint32_t bar, int bytes) {
  asm volatile("mbarrier.arrive.expect_tx.shared::cta.b64 _, [%0], %1;\n" ::"r"(bar), "r"(bytes) : "memory");
}
__device__ __forceinline__ void mbar_wait(uint32_t bar, uint32_t parity) {
  asm volatile(
      "{\n.reg .pred p;\n"
      "WAIT_%=:\n"
      "mbarrier.try_wait.parity.shared::cta.b64 p, [%0], %1;\n"
      "@p bra DONE_%=;\n"
      "bra WAIT_%=;\n"
      "DONE_%=:\n}\n" ::"r"(bar), "r"(parity) : "memory");
}
__device__ __forceinline__ void tma_load_2d(uint32_t dst, const CUtensorMap* tm, int c0, int c1, uint32_t bar) {
  asm volatile("cp.async.bulk.tensor.2d.shared::cluster.global.mbarrier::complete_tx::bytes [%0], [%1, {%3, %4}], [%2];\n" ::"r"(dst),
               "l"(tm), "r"(bar), "r"(c0), "r"(c1) : "memory");
}
__device__ __forceinline__ void tma_load_3d(uint32_t dst, const CUtensorMap* tm, int c1, uint32_t bar) {
  asm volatile("cp.async.bulk.tensor.3d.shared::cluster.global.mbarrier::complete_tx::bytes [%0], [%1, {0, %3, 0}], [%2];\n" ::"r"(dst),
               "l"(tm), "r"(bar), "r"(c1) : "memory");
}
__device__ __forceinline__ bool elect_one() {
  uint32_t p;
  asm volatile("{\n.reg .pred p;\nelect.sync _|p, 0xffffffff;\nselp.u32 %0, 1, 0, p;\n}\n" : "=r"(p));
  return p;
}
__device__ __forceinline__ void tma_store_2d(const CUtensorMap* tm, uint32_t src, int c0, int c1) {
  asm volatile("cp.async.bulk.tensor.2d.global.shared::cta.bulk_group [%0, {%2, %3}], [%1];\n" ::"l"(tm), "r"(src), "r"(c0), "r"(c1) : "memory");
}

template <int N, int FIRST, int S0 = 0, int S1 = 8>
__device__ __forceinline__ void proj(float (&acc)[52], const uint32_t (&w)[32], uint64_t de) {
  wg_fence();
#pragma unroll
  for (int s = S0; s < S1; s++) {
    uint64_t db = de + (uint64_t)(((s >> 2) * N * 128 + (s & 3) * 32) >> 4);
    if (s == 0) mma_rs<N, FIRST>(acc, w[0], w[1], w[2], w[3], db);
    else mma_rs<N, 1>(acc, w[4 * s], w[4 * s + 1], w[4 * s + 2], w[4 * s + 3], db);
  }
  wg_commit();
}
__device__ __forceinline__ void issue_pv(float (&a)[52], const uint32_t (&vf)[28], uint64_t dp) {
  wg_fence();
#pragma unroll
  for (int s = 0; s < 6; s++) mma_rs<104, 1>(a, vf[4 * s], vf[4 * s + 1], vf[4 * s + 2], vf[4 * s + 3], dp + 16 * s);
  mma_rs<104, 1>(a, vf[24], vf[25], vf[26], vf[27], (dp + 16 * 6) & ~((uint64_t)0x3FFF << 16));
  wg_commit();
}
__device__ __forceinline__ void issue_s(float (&acc)[52], uint64_t dq, uint64_t dk) {
  wg_fence();
#pragma unroll
  for (int s = 0; s < 4; s++) {
    if (s == 0) mma_ss<false>(acc, dq, dk);
    else mma_ss<true>(acc, dq + 2 * s, dk + 2 * s);
  }
  wg_commit();
}

__device__ __forceinline__ void sched_barrier() { asm volatile("pmevent 1;\n" ::: "memory"); }
#define PINR(x) asm volatile("" : "+r"(x)::"memory")
#define PIN(x) asm volatile("" : "+f"(x)::"memory")

constexpr float kC = 0.125f * 1.4426950408889634f;

__device__ __forceinline__ bool out_of_range(float t) { return !(t >= 0x1p-30f && t <= 0x1p30f); }
__device__ __forceinline__ uint32_t mul_bf16x2(uint32_t a, uint32_t b) {
  uint32_t r;
  asm("mul.rn.bf16x2 %0, %1, %2;\n" : "=r"(r) : "r"(a), "r"(b));
  return r;
}
__device__ __forceinline__ uint32_t add_bf16x2(uint32_t a, uint32_t b) {
  uint32_t r;
  asm("add.rn.bf16x2 %0, %1, %2;\n" : "=r"(r) : "r"(a), "r"(b));
  return r;
}
__device__ __forceinline__ uint32_t quad_bcast(uint32_t v, uint32_t code) {
  uint32_t r;
  asm volatile("shfl.sync.idx.b32 %0, %1, %2, 0x31f, 0xffffffff;\n" : "=r"(r) : "r"(v), "r"(code));
  return r;
}
__device__ __forceinline__ float quad_sum(float t) {
  t += __shfl_xor_sync(0xffffffffu, t, 1);
  t += __shfl_xor_sync(0xffffffffu, t, 2);
  return t;
}
struct Q3 { float t, s1, s2, s3; };
__device__ __forceinline__ Q3 q3_start(float t) {
  Q3 q;
  q.t = t;
  q.s1 = __shfl_xor_sync(0xffffffffu, t, 1);
  q.s2 = __shfl_xor_sync(0xffffffffu, t, 2);
  q.s3 = __shfl_xor_sync(0xffffffffu, t, 3);
  return q;
}
__device__ __forceinline__ float q3_end(const Q3& q) { return (q.t + q.s1) + (q.s2 + q.s3); }
template <int O, int J0, int J1>
__device__ __forceinline__ void part_exp(const float (&s)[52], uint32_t (&p)[13], bool tail_invalid, float& t0, float& t1) {
#pragma unroll
  for (int j = J0; j < J1; j++) {
    const int jj = (j + 12) % 13;
    float x = ex2(s[4 * jj + O]), y = ex2(s[4 * jj + O + 1]);
    if (jj == 12 && tail_invalid) { x = 0.f; y = 0.f; }
    p[jj] = pack_bf16(x, y);
    if (j == 0) { t0 = x; t1 = y; } else { t0 += x; t0 += y; }
  }
}
template <int O>
__device__ __forceinline__ float set_max(const float (&s)[52], bool tail_invalid) {
  float m = fmaxf(s[O], s[O + 1]);
#pragma unroll
  for (int j = 1; j < 12; j++) m = fmaxf(m, fmaxf(s[4 * j + O], s[4 * j + O + 1]));
  if (!tail_invalid) m = fmaxf(m, fmaxf(s[48 + O], s[49 + O]));
  m = fmaxf(m, __shfl_xor_sync(0xffffffffu, m, 1));
  return fmaxf(m, __shfl_xor_sync(0xffffffffu, m, 2));
}
template <int O>
__device__ __forceinline__ float set_exact(const float (&s)[52], uint32_t (&p)[13], bool tail_invalid, float m) {
  float t0, t1;
#pragma unroll
  for (int j = 0; j < 13; j++) {
    const int jj = (j + 12) % 13;
    float x = ex2(s[4 * jj + O] - m), y = ex2(s[4 * jj + O + 1] - m);
    if (jj == 12 && tail_invalid) { x = 0.f; y = 0.f; }
    p[jj] = pack_bf16(x, y);
    if (j == 0) { t0 = x; t1 = y; } else { t0 += x; t1 += y; }
  }
  return quad_sum(t0 + t1);
}
__device__ __forceinline__ uint32_t inv2(float t) { const float iv = rcp(t); return pack_bf16(iv, iv); }
template <int C>
__device__ __forceinline__ void part_store(const uint32_t (&p)[13], uint32_t iv, uint32_t paddr) {
  if (C < 3) stsm_x4(paddr + C * 512, mul_bf16x2(p[4 * C], iv), mul_bf16x2(p[4 * C + 1], iv), mul_bf16x2(p[4 * C + 2], iv), mul_bf16x2(p[4 * C + 3], iv));
  else stsm_x1(paddr + 1536, mul_bf16x2(p[12], iv));
}
__device__ __forceinline__ void set_store(const uint32_t (&p)[13], float t, uint32_t paddr) {
  const uint32_t iv = inv2(t);
  part_store<0>(p, iv, paddr);
  part_store<1>(p, iv, paddr);
  part_store<2>(p, iv, paddr);
  part_store<3>(p, iv, paddr);
}

struct Params {
  const uint8_t* w[4];
  uint8_t* out;
  unsigned* claim;
  short n_pairs, n_extra, n_open, streams;
};
struct Maps { CUtensorMap m[8]; };
template <int V> using IC = std::integral_constant<int, V>;
using I104 = std::integral_constant<int, 104>;
using I96 = std::integral_constant<int, 96>;

__global__ void __launch_bounds__(512, 1)
autoint_kernel(const __grid_constant__ Params prm, const __grid_constant__ Maps tm) {
  extern __shared__ __align__(1024) uint8_t smem[];
  const uint32_t sbase = smem_u32(smem);
  const int tid = threadIdx.x;
  const uint32_t bar_full = sbase + kBarOff;
  const uint32_t bar_w = sbase + kBarOff + 64;
  const int cta = blockIdx.x, stream = cta >> 1, head = cta & 1;
  if (tid >= 256 && tid < 448) {
    if ((tid & 31) == 0) {
      const int k = (tid >> 5) - 8, m = (0x402153 >> (4 * (5 - k))) & 15;
      const uint32_t bar = m == 5 ? bar_full : bar_w + 8 * m;
      const uint32_t dst = sbase + (m == 0 ? kPOff : m == 1 ? kWkOff : m < 4 ? (m + 1) * kEStage : (m - 4) * kEHalf);
      const int c0 = m == 3 ? head * 64 : m == 5 ? 64 : 0, c1 = m < 3 ? head * 128 : m == 3 ? 0 : stream * 2 * kF;
      mbar_init(bar, 1);
      asm volatile("fence.mbarrier_init.release.cluster;\n" ::: "memory");
      fence_async();
      const long long c = clock64();
      while (clock64() - c < k * 60) {}
      mbar_expect_tx(bar, m < 4 ? 16384 : kEHalf);
      tma_load_2d(dst, &tm.m[3 + min(m, 4)], c0, c1, bar);
    }
  } else if (tid == 448) {
    for (int s = 1; s < kStages; s++) mbar_init(bar_full + 8 * s, 1);
    asm volatile("fence.mbarrier_init.release.cluster;\n" ::: "memory");
    asm volatile("st.shared.v2.u32 [%0], {%1,%1};\n" ::"r"(sbase + kZeroOff), "r"(0) : "memory");
    fence_async();
  } else if (tid < 192) {
    if (tid < 96 && (tid & 31) == 0) asm volatile("prefetch.tensormap [%0];\n" ::"l"(&tm.m[tid >> 5]) : "memory");
  } else if (tid >= 224) {
    if (tid < 250) asm volatile("st.shared.v4.u32 [%0], {%1,%1,%1,%1};\nst.shared.v4.u32 [%0 + 16], {%1,%1,%1,%1};\n"
                                ::"r"(sbase + kPOff + 12 * kPGrp + ((tid - 224) >> 1) * 128 + 64 + (tid & 1) * 32), "r"(0) : "memory");
  } else if (tid < 200) {
    asm volatile("prefetch.global.L2 [%0];\n" ::"l"(prm.w[(cta >> 5) & 3] + (cta & 31) * 1024 + (tid & 7) * 128) : "memory");
  }
  const int wg = __shfl_sync(0xffffffffu, tid >> 7, 0);
  __syncthreads();
  sched_barrier();
  const int n_pairs = prm.n_pairs, n_open = prm.n_open, streams = prm.streams;
  const int n_static = 2 * (n_pairs + (stream < prm.n_extra));
  const int n_tiles = n_static + (n_open > 0);
  auto row_of = [&](int i) {
    return i < n_static ? (((i >> 1) * streams + stream) * 2 + (i & 1)) * kF : lds(sbase + kCntOff + 4);
  };
  auto load_e = [&](int i, int st, int row) {
    mbar_expect_tx(bar_full + 8 * st, (i & 1) ? 2 * 96 * 128 : 2 * 104 * 128);
    tma_load_3d(sbase + st * kEStage, &tm.m[i & 1], row + (i & 1) * 4, bar_full + 8 * st);
  };
  auto next_row = [&](int i, int row) { return row + ((i & 1) ? (2 * streams - 1) * kF : kF); };
  auto read_count = [&]() { return __shfl_sync(0xffffffffu, lds(sbase + kCntOff), 0); };

#define ROLE_IDS()                                                                                     \
  int rtid;                                                                                            \
  asm volatile("mov.u32 %0, %tid.x;\n" : "=r"(rtid));                                                  \
  const int lane = rtid & 31;                                                                          \
  [[maybe_unused]] const int warp = __shfl_sync(0xffffffffu, (rtid >> 5) & 3, 0);                      \
  [[maybe_unused]] const uint32_t chunk = ((rtid >> 4) & 6) + ((lane >> 3) & 1);                       \
  [[maybe_unused]] const uint32_t t_off = ((lane >> 4) * 8 + (lane & 7)) * 128 + ((chunk ^ (lane & 7)) << 4)
  auto load_frags = [&](uint32_t (&w)[32], int m, uint32_t addr) {
    mbar_wait(bar_w + 8 * m, 0);
#pragma unroll
    for (int s = 0; s < 8; s++) ldsm_x4_t(addr + s * 2048, w[4 * s], w[4 * s + 1], w[4 * s + 2], w[4 * s + 3]);
  };
  const uint64_t dE0 = desc_sw128(sbase);
  auto finish = [&](int n_items) {
    int rtid;
    asm volatile("mov.u32 %0, %tid.x;\n" : "=r"(rtid));
    uint8_t* dst = prm.out + (size_t)row_of(n_items - 1) * (kD * 2) + head * 128;
    asm volatile("barrier.cta.sync %0, 512;\n" ::"n"((int)BAR_W) : "memory");
#pragma unroll
    for (int k = 0; k < 2; k++) {
      const int c = rtid + 512 * k, r = c >> 3;
      if (c < 8 * kF) {
        uint4 v;
        asm volatile("ld.shared.v4.u32 {%0,%1,%2,%3}, [%4];\n" : "=r"(v.x), "=r"(v.y), "=r"(v.z), "=r"(v.w)
                     : "r"(sbase + kQOff + r * 128 + (((c ^ r) & 7) << 4)) : "memory");
        *(uint4*)(dst + r * (kD * 2) + (c & 7) * 16) = v;
      }
    }
  };

  if (wg == 0) {
    asm volatile("setmaxnreg.inc.sync.aligned.u32 144;\n");
    ROLE_IDS();
    uint32_t wQ[32], wK[32];
    float acc[52];
    load_frags(wQ, 0, sbase + kPOff + t_off);
#pragma unroll
    for (int i = 0; i < 32; i++) wQ[i] = pack_bf16(__uint_as_float(wQ[i] << 16) * kC, __uint_as_float(wQ[i] & 0xffff0000u) * kC);
    int n_items = n_static;
    const uint32_t k_addr = sbase + kKOff + t_off, q_addr = sbase + kQOff + t_off;
    uint32_t pk[26];
    uint32_t e_off = 0, e_bar = bar_full, e_ph = 0;
    auto pack = [&](auto NC) {
      constexpr int N = decltype(NC)::value;
      wg_wait<0>();
      fence_acc<N>(acc);
#pragma unroll
      for (int i = 0; i < N / 4; i++) pk[i] = pack_bf16(acc[2 * i], acc[2 * i + 1]);
    };
    const bool server = warp == kStore;
    auto serve = [&](int it, int row) {
      bar_sync(BAR_O, 160);
      if (elect_one()) {
        fence_async();
        tma_store_2d(&tm.m[2], sbase + kOOff, head * 64, row);
        asm volatile("cp.async.bulk.commit_group;\n" ::: "memory");
      }
    };
    auto release_o = [&]() {
      asm volatile("cp.async.bulk.wait_group.read 0;\n" ::: "memory");
      __syncwarp();
      bar_arrive(BAR_OF, 160);
    };
    int st_row = 2 * stream * kF;
    auto publish = [&](int it) {
      const int n = it >= 2 ? 384 : 256;
      fence_async();
      bar_arrive(BAR_X, n);
      if (it < 2) bar_arrive(BAR_X + 1, 256);
    };
    auto item = [&](auto NC, auto FC, int it) {
      constexpr int N = decltype(NC)::value;
      constexpr bool first = decltype(FC)::value;
      constexpr int kPre = first ? 4 : 8;
      const uint64_t dE = dE0 + e_off;
      auto store_q = [&](int j0, int j1) {
#pragma unroll
        for (int j = j0; j < j1; j += 2) {
          if (j < 12) stsm_x4_t(q_addr + j * 1024, pk[2 * j], pk[2 * j + 1], pk[2 * j + 2], pk[2 * j + 3]);
          else if (N == 104) stsm_x2_t(q_addr + 12 * 1024, pk[24], pk[25]);
        }
      };
      if (first) {
        mbar_wait(bar_w + 32, 0);
        proj<N, 0, 0, 4>(acc, wQ, dE);
        bar_arrive(BAR_T1, 256);
        load_frags(wK, 1, q_addr + (kWkOff - kQOff));
        mbar_wait(bar_full, 0);
        proj<N, 0, 4, 8>(acc, wQ, dE);
        bar_arrive(BAR_S1, 256);
      } else {
        if (it >= 3) bar_sync(BAR_T1, 256);
        proj<N, 0>(acc, wQ, dE);
        if (N == 104 || it > 1) publish(it - 1);
        if (server && it >= 4) release_o();
      }
      pack(NC);
#pragma unroll
      for (int i = 0; i < N / 4; i++) asm volatile("" : "+r"(pk[i])::"memory");
      sched_barrier();
      if (!first) bar_sync(BAR_QE, 256);
      store_q(0, kPre);
      if (!first) bar_sync(BAR_SP + 1, 256);
      proj<N, 2>(acc, wK, dE);
      if (!first && (N == 104 || it > 1)) bar_arrive(BAR_S2, 256);
      if (first) bar_arrive(BAR_O, 256);
      store_q(kPre, 8);
      e_off += kEStage >> 4;
      e_bar += 8;
      if (e_off == kStages * (kEStage >> 4)) { e_off = 0; e_bar = bar_full; e_ph ^= 1; }
      if (!first) {
        if (it + 1 < n_tiles) mbar_wait(e_bar, e_ph);
        bar_sync(BAR_QE + 1, 256);
      }
      store_q(8, 14);
      if (!first && it >= 3) {
        if (server) serve(it - 3, st_row);
        st_row = next_row(it - 3, st_row);
      }
      if (N == 96 && it + 1 == n_static) n_items = read_count();
      pack(NC);
#pragma unroll
      for (int j = 0; j < 12; j += 2) stsm_x4_t(k_addr + j * 1024, pk[2 * j], pk[2 * j + 1], pk[2 * j + 2], pk[2 * j + 3]);
      if (N == 104) stsm_x2_t(k_addr + 12 * 1024, pk[24], pk[25]);
      if (!first && (N == 104 || it > 1)) bar_arrive(BAR_X + 1, 256);
      if (first) {
        fence_async();
        bar_arrive(BAR_X, 256);
        mbar_wait(bar_full + 8, 0);
        bar_sync(BAR_SP, 256);
        bar_arrive(BAR_X + 1, 256);
      }
    };
    item(I104{}, std::true_type{}, 0);
    for (int it = 1;; it += 2) {
      item(I96{}, std::false_type{}, it);
      if (it + 1 == n_items) break;
      item(I104{}, std::false_type{}, it + 1);
      if (it + 2 == n_items) break;
    }
    publish(n_items - 1);
    if (server) {
      for (int it = n_items - 3; it < n_items - 1; it++) {
        release_o();
        serve(it, st_row);
        st_row = next_row(it, st_row);
      }
    }
    finish(n_items);
    asm volatile("cp.async.bulk.wait_group.read 0;\n" ::: "memory");
  } else if (wg == 1) {
    asm volatile("setmaxnreg.inc.sync.aligned.u32 176;\n");
    ROLE_IDS();
    uint32_t wV[32], wR[32];
    float acc[52];
    uint32_t vf[28], pl[2];
    asm volatile("ld.volatile.shared.v2.u32 {%0, %1}, [%2];\n" : "=r"(vf[26]), "=r"(vf[27]) : "r"(sbase + kZeroOff) : "memory");
    load_frags(wV, 2, sbase + 3 * kEStage + t_off);
    int n_items = n_static;
    const uint32_t o_even = sbase + kOOff + t_off;
    const uint32_t r4 = (lane & 7) + 4;
    const uint32_t o_odd = sbase + kOOff + ((lane >> 4) * 8 + r4) * 128 + ((chunk ^ (r4 & 7)) << 4) + vf[26];
    const uint32_t o_odd_last = sbase + kOOff + ((lane & 4) ? (r4 & 7) : 96 + r4) * 128 + ((chunk ^ (r4 & 7)) << 4) + vf[26];
    const uint64_t dP = desc_p(sbase + kPOff);
    uint32_t e_off = 0;
    auto store_o = [&](int par, int it, int j0, int j1) {
      const uint32_t a = par ? o_odd : o_even;
      if (j0 == 0 && it >= 1) bar_sync(BAR_OF, 160);
#pragma unroll
      for (int j = j0; j < j1; j += 2) {
        if (j < 12) stsm_x4_t(a + j * 1024, vf[2 * j], vf[2 * j + 1], vf[2 * j + 2], vf[2 * j + 3]);
        else stsm_x2_t(par ? o_odd_last : o_even + 12 * 1024, pl[0], pl[1]);
      }
    };
    auto item = [&](auto NC, auto FC, int it) {
      constexpr int N = decltype(NC)::value, par = N == 96;
      constexpr bool first = decltype(FC)::value;
      const uint64_t dE = dE0 + e_off;
      if (first) {
        mbar_wait(bar_w + 32, 0);
        bar_sync(BAR_T1, 256);
        proj<N, 0, 0, 4>(acc, wV, dE);
        mbar_wait(bar_full, 0);
        bar_sync(BAR_S1, 256);
        proj<N, 0, 4, 8>(acc, wV, dE);
        load_frags(wR, 3, o_even + (4 * kEStage - kOOff));
        bar_arrive(BAR_W, 160);
      } else {
#pragma unroll
        for (int i = 0; i < 24; i++) asm volatile("" : "+r"(vf[i])::"memory");
        asm volatile("" : "+r"(pl[0]), "+r"(pl[1])::"memory");
        sched_barrier();
        if (it + 1 < n_items) bar_sync(BAR_SP, 256);
        proj<N, 2>(acc, wV, dE);
        if (it + 1 < n_items) bar_arrive(BAR_S1, 256);
        store_o(par ^ 1, it - 1, 0, 6);
        if (it + 1 < n_items) {
          bar_sync(BAR_PF + par, 384);
          fence_async();
        }
        if (par && it + 3 == n_static) n_items = read_count();
        store_o(par ^ 1, it - 1, 6, 14);
        bar_arrive(BAR_O, 160);
      }
      wg_wait<0>();
      fence_acc<N>(acc);
#pragma unroll
      for (int i = 0; i < N / 4; i++) {
        if (!first) asm("cvt.rn.bf16x2.f32 %0, %1, %2;\n" : "+r"(vf[i]) : "f"(acc[2 * i + 1]), "f"(acc[2 * i]));
        else vf[i] = pack_bf16(acc[2 * i], acc[2 * i + 1]);
      }
      if (first) bar_sync(BAR_O, 256);
      else {
#pragma unroll
        for (int i = 0; i < N / 4; i++) asm volatile("" : "+r"(vf[i])::"memory");
        sched_barrier();
        if (it + 2 < n_items) bar_sync(BAR_S2, 256);
      }
      proj<N, 2>(acc, wR, dE);
      if (first) {
        bar_sync(BAR_PF + par, 384);
        fence_async();
        bar_sync(BAR_SP, 256);
        bar_sync(BAR_S2, 256);
      }
      if (!first && it + 1 >= n_items) {
        bar_sync(BAR_PF + par, 384);
        fence_async();
      }
      issue_pv(acc, vf, dP + (uint64_t)((par * kPBuf) >> 4));
      if (it + 3 < n_items) bar_arrive(BAR_T1, 256);
      e_off = e_off == (kStages - 1) * (kEStage >> 4) ? 0 : e_off + (kEStage >> 4);
      wg_wait<0>();
      if (it + 2 < n_items) bar_arrive(BAR_X, 384);
      sched_barrier();
      fence_acc(acc);
#pragma unroll
      for (int i = 0; i < 24; i++) asm("cvt.rn.relu.bf16x2.f32 %0, %1, %2;\n" : "+r"(vf[i]) : "f"(acc[2 * i + 1]), "f"(acc[2 * i]));
      pl[0] = pack_bf16_relu(acc[48], acc[49]);
      pl[1] = pack_bf16_relu(acc[50], acc[51]);
    };
    item(I104{}, std::true_type{}, 0);
    for (int it = 1;; it += 2) {
      item(I96{}, std::false_type{}, it);
      if (it + 1 == n_items) break;
      item(I104{}, std::false_type{}, it + 1);
      if (it + 2 == n_items) break;
    }
    {
      const int par = (n_items - 1) & 1;
      const uint32_t a = (par ? o_odd : o_even) + (kQOff - kOOff);
#pragma unroll
      for (int j = 0; j < 12; j += 2) stsm_x4_t(a + j * 1024, vf[2 * j], vf[2 * j + 1], vf[2 * j + 2], vf[2 * j + 3]);
      stsm_x2_t((par ? o_odd_last : o_even + 12 * 1024) + (kQOff - kOOff), pl[0], pl[1]);
    }
    finish(n_items);
  } else {
    if (wg == 2) {
      asm volatile("setmaxnreg.dec.sync.aligned.u32 96;\n");
      ROLE_IDS();
      const uint64_t dK = desc_sw128(sbase + kKOff);
      float acc[52];
      const uint64_t dQ = desc_sw128(sbase + kQOff);
      uint32_t pa = sbase + kPOff + 2 * warp * kPGrp + lane * 16;
      int tail = (lane >> 1) & 1;
      if (rtid == 256) {
        mbar_wait(bar_w, 0);
        load_e(1, 1, row_of(1));
        mbar_wait(bar_full, 0);
        load_e(2, 2, row_of(2));
      }
      if (rtid == 320) {
        const int m = max(n_open, 1), x = stream % m;
        asm volatile("st.shared.v4.u32 [%0], {%1,%2,%3,%4};\n" ::"r"(sbase + kCntOff), "r"(n_static), "r"((2 * n_pairs * streams + x) * kF),
                     "r"(2 * x + head), "r"((streams - 1 - x) / m) : "memory");
      }
      if (warp == kServe) bar_sync(BAR_W, 160);
      __syncwarp();
      int n_items = n_static;
      int ld_row = (2 * (streams + stream) + 1) * kF, ld_st = 3;
      uint32_t ticket = 1;
      for (int it = 0; it < n_items; it++) {
        bar_sync(BAR_X, it >= 2 ? 384 : 256);
        issue_s(acc, dQ, dK);
        bar_arrive(BAR_SP, 256);
        if (warp == kServe && it + 3 < n_tiles) {
          if (it + 3 == n_static) ld_row = __shfl_sync(0xffffffffu, lds(sbase + kCntOff + 4), 0);
          if (elect_one()) load_e(it + 3, ld_st, ld_row);
        }
        ld_row = next_row(it + 3, ld_row);
        ld_st = ld_st == kStages - 1 ? 0 : ld_st + 1;
        if (it + 1 == n_static) n_items = read_count();
        wg_wait<0>();
        if (it + 1 < n_items) bar_arrive(BAR_QE, 256);
        if (ticket == 0) asm volatile("st.shared.u32 [%0], %1;\n" ::"r"(sbase + kCntOff), "r"(it + 5) : "memory");
        sched_barrier();
        fence_acc(acc);
        uint32_t p0[13], p1[13];
        float t0, t1, u0, u1;
        part_exp<0, 0, 13>(acc, p0, tail, t0, u0);
        part_exp<2, 0, 2>(acc, p1, tail, t1, u1);
        t0 += u0;
        u0 = __shfl_xor_sync(0xffffffffu, t0, 1);
        PIN(t1); PIN(u1);
        sched_barrier();
        part_exp<2, 2, 6>(acc, p1, tail, t1, u1);
        PIN(t1); PIN(u1);
        sched_barrier();
        t0 += u0;
        u0 = __shfl_xor_sync(0xffffffffu, t0, 2);
        sched_barrier();
        part_exp<2, 6, 10>(acc, p1, tail, t1, u1);
        PIN(t1); PIN(u1);
        sched_barrier();
        t0 += u0;
        const uint32_t i0 = inv2(t0);
        part_store<0>(p0, i0, pa);
        part_exp<2, 10, 13>(acc, p1, tail, t1, u1);
        const Q3 q1 = q3_start(t1 + u1);
        sched_barrier();
        part_store<1>(p0, i0, pa);
        part_store<2>(p0, i0, pa);
        part_store<3>(p0, i0, pa);
        sched_barrier();
        t1 = q3_end(q1);
        if (__builtin_expect(__any_sync(0xffffffffu, out_of_range(t0) || out_of_range(t1)), 0)) {
          set_store(p0, set_exact<0>(acc, p0, tail, set_max<0>(acc, tail)), pa);
          t1 = set_exact<2>(acc, p1, tail, set_max<2>(acc, tail));
        }
        set_store(p1, t1, pa + kPGrp);
        bar_arrive(BAR_PF + (it & 1), 384);
        ticket = 1;
        if (it + 5 == n_static && n_open > 0 && warp == kClaim) {
          if (elect_one())
            asm volatile("atom.global.inc.u32 %0, [%1], %2;\n" : "=r"(ticket) : "l"(prm.claim + lds(sbase + kCntOff + 8)), "r"(lds(sbase + kCntOff + 12)) : "memory");
        }
        pa += (it & 1) ? -kPBuf : kPBuf;
        tail ^= 1;
      }
      finish(n_items);
    } else {
      asm volatile("setmaxnreg.dec.sync.aligned.u32 96;\n");
      ROLE_IDS();
      const uint64_t dQ = desc_sw128(sbase + kQOff + 8192);
      uint32_t k_addr = sbase + kKOff + ((lane & 8) ? 12 : 8 + warp) * 1024 + (lane & 7) * 128 + (((lane >> 4) ^ (lane & 7)) << 4);
      const uint32_t pa = sbase + kPOff + (8 + (lane >> 3)) * kPGrp + 2 * warp * 128 + (lane & 7) * 16 + kPBuf;
      const uint32_t trash = sbase + kTrashOff + lane * 16;
      const uint32_t pd = sbase + kPOff + (lane < 24 ? 12 * kPGrp + (lane < 16 ? 2 * warp + (lane >> 3) : 8 + warp) * 128 : (8 + warp) * kPGrp + 12 * 128) + (lane & 7) * 16;
      uint32_t pd0 = lane >= 24 || (lane & 4) ? pd + kPBuf : trash;
      const uint32_t pdx = pd0 ^ (lane >= 24 || !(lane & 4) ? pd : trash);
      uint32_t sum_addr = sbase + kSumOff + lane * 16;
      asm volatile("xor.b32 %0, %0, %1;\n" : "+r"(sum_addr) : "r"(lds(sbase + kZeroOff)));
      const uint32_t d_code = ((warp & 1) << 4) | ((warp & 2) << 2);
      int n_items = n_static;
      uint32_t kf[16 + 4 * kRs];
      uint32_t k0_addr = sbase + kKOff + (2 * warp + ((lane >> 3) & 1)) * 1024 + (lane & 7) * 128 + (((lane >> 4) ^ (lane & 7)) << 4);
      asm volatile("xor.b32 %0, %0, %2;\nxor.b32 %1, %1, %2;\n" : "+r"(k_addr), "+r"(k0_addr) : "r"(lds(sbase + kZeroOff)));
      const uint64_t dK = desc_sw128(sbase + kKOff);
      auto load_k = [&](bool more, auto S0, auto S1) {
        constexpr int s0 = decltype(S0)::value, s1 = decltype(S1)::value;
        if (s0 == 0 && more) bar_sync(BAR_X + 1, 256);
#pragma unroll
        for (int s = s0; s < s1; s++) {
          uint32_t a = s < 4 ? k_addr : k0_addr;
          if (s & 3) asm volatile("xor.b32 %0, %1, %2;\n" : "=r"(a) : "r"(s < 4 ? k_addr : k0_addr), "r"((s & 3) << 5));
          ldsm_x4(a, kf + 4 * s);
        }
      };
      load_k(true, IC<0>{}, IC<4 + kRs>{});
      for (int it = 0; it < n_items; it++) {
        float t0[20], t1[20];
        if (it >= 2) bar_sync(BAR_S1, 256);
        wg_fence();
#pragma unroll
        for (int s = 0; s < 4; s++) {
          if (s) mma_rs40<true>(t1, kf + 4 * s, dQ + 2 * s); else mma_rs40<false>(t1, kf, dQ);
          if (s < kRs) { if (s) mma_rs40<true>(t0, kf + 16 + 4 * s, dQ + 2 * s); else mma_rs40<false>(t0, kf + 16, dQ); }
          else mma_ss40(t0, dK + 2 * s, dQ + 2 * s);
        }
        wg_commit();
        if (it + 1 < n_items) bar_arrive(BAR_SP + 1, 256);
        sched_barrier();
        pd0 ^= pdx;
        PINR(pd0);
        const uint32_t po = (it & 1) * kPBuf - kPBuf;
        if (it + 2 == n_static) n_items = read_count();
        sched_barrier();
        wg_wait<0>();
        if (it + 1 < n_items) bar_arrive(BAR_QE + 1, 256);
        sched_barrier();
        asm volatile("" : ACC20_OPS("+f", t0)::"memory");
        asm volatile("" : ACC20_OPS("+f", t1)::"memory");
        const bool b4 = sum_addr & 256, b3 = sum_addr & 128, b2 = sum_addr & 64;
        const bool tail = (sum_addr ^ (it << 5)) & 32, other = (sum_addr ^ (it << 8)) & 256;
        uint32_t pA[5], pB[5], pC[5], d0, d1, iv;
        for (int pass = 0;; pass++) {
          auto d_part = [&]() {
            float a0, a1;
            if (warp & 2) { if (warp & 1) { a0 = ex2(t1[14]); a1 = ex2(t1[15]); } else { a0 = ex2(t1[10]); a1 = ex2(t1[11]); } }
            else { if (warp & 1) { a0 = ex2(t1[6]); a1 = ex2(t1[7]); } else { a0 = ex2(t1[2]); a1 = ex2(t1[3]); } }
            d0 = pack_bf16(a0, a1);
            d1 = pack_bf16(ex2(t1[18]), ex2(t1[19]));
            if (other) d0 = 0;
            if (other || warp != 3) d1 = 0;
          };
          d_part();
          auto col = [&](int j) {
            pA[j] = pack_bf16(ex2(t0[4 * j]), ex2(t0[4 * j + 1]));
            pB[j] = pack_bf16(ex2(t0[4 * j + 2]), ex2(t0[4 * j + 3]));
            pC[j] = pack_bf16(ex2(t1[4 * j]), ex2(t1[4 * j + 1]));
            uint32_t z = add_bf16x2(add_bf16x2(pA[j], pB[j]), pC[j]);
            if (j == 4) z = add_bf16x2(z, d1);
            else if (warp == j) z = add_bf16x2(z, d0);
            return z;
          };
          const uint32_t z4 = col(4), z0 = col(0), z1 = col(1);
          const uint32_t s4 = __shfl_xor_sync(0xffffffffu, z4, 16);
          const uint32_t k0 = b4 ? z1 : z0, s0 = __shfl_xor_sync(0xffffffffu, b4 ? z0 : z1, 16);
          const uint32_t z2 = col(2), z3 = col(3);
          const uint32_t y0 = add_bf16x2(k0, s0), y2 = add_bf16x2(z4, s4);
          const uint32_t y1 = add_bf16x2(b4 ? z3 : z2, __shfl_xor_sync(0xffffffffu, b4 ? z2 : z3, 16));
          const uint32_t x1 = add_bf16x2(y2, __shfl_xor_sync(0xffffffffu, y2, 8));
          const uint32_t x0 = add_bf16x2(b3 ? y1 : y0, __shfl_xor_sync(0xffffffffu, b3 ? y0 : y1, 8));
          uint4 u;
          const uint32_t w = add_bf16x2(b2 ? x1 : x0, __shfl_xor_sync(0xffffffffu, b2 ? x0 : x1, 4));
          asm volatile("{\n.reg .u32 a;\nadd.u32 a, %0, %2;\nst.shared.u32 [a], %1;\n}\n" ::"r"(sum_addr), "r"(w), "r"(warp * 4) : "memory");
          bar_sync(BAR_D, 128);
          asm volatile("ld.shared.v4.u32 {%0,%1,%2,%3}, [%4];\n" : "=r"(u.x), "=r"(u.y), "=r"(u.z), "=r"(u.w) : "r"(sum_addr) : "memory");
          load_k(it + 1 < n_items && !pass, IC<0>{}, IC<4>{});
          u.x = add_bf16x2(u.x, u.y);
          u.z = add_bf16x2(u.z, u.w);
          const float lo = __uint_as_float(u.x << 16) + __uint_as_float(u.z << 16);
          const float hi = __uint_as_float(u.x & 0xffff0000u) + __uint_as_float(u.z & 0xffff0000u);
          iv = pack_bf16(rcp(lo), rcp(hi));
          if (__builtin_expect(!__any_sync(0xffffffffu, !(b2 && tail) && (out_of_range(lo) | out_of_range(hi))) || pass, 1)) break;
          float m[10];
          const uint32_t max_addr = sbase + kMaxOff + (((sum_addr + lds(sbase + kZeroOff)) >> 4) & 3) * 192;
#pragma unroll
          for (int k = 0; k < 10; k++) {
            const int i = 4 * (k >> 1) + (k & 1);
            m[k] = fmaxf(fmaxf(t0[i], t0[i + 2]), other ? t1[i] : fmaxf(t1[i], t1[i + 2]));
            m[k] = fmaxf(m[k], __shfl_xor_sync(0xffffffffu, m[k], 4));
            m[k] = fmaxf(m[k], __shfl_xor_sync(0xffffffffu, m[k], 8));
            m[k] = fmaxf(m[k], __shfl_xor_sync(0xffffffffu, m[k], 16));
            asm volatile("st.shared.f32 [%0], %1;\n" ::"r"(max_addr + k * 16 + warp * 4), "f"(m[k]) : "memory");
          }
          bar_sync(BAR_D, 128);
#pragma unroll
          for (int k = 0; k < 10; k++) {
            const int i = 4 * (k >> 1) + (k & 1);
            float4 v;
            asm volatile("ld.shared.v4.f32 {%0,%1,%2,%3}, [%4];\n" : "=f"(v.x), "=f"(v.y), "=f"(v.z), "=f"(v.w) : "r"(max_addr + k * 16) : "memory");
            const float mk = fmaxf(fmaxf(v.x, v.y), fmaxf(v.z, v.w));
            t0[i] -= mk; t0[i + 2] -= mk; t1[i] -= mk; t1[i + 2] -= mk;
          }
        }
        const uint32_t i0 = quad_bcast(iv, 0), i1 = quad_bcast(iv, 16), i2 = quad_bcast(iv, 8), i3 = quad_bcast(iv, 24);
        const uint32_t i4 = quad_bcast(iv, 4), id = quad_bcast(iv, d_code);
        stsm_x4_t(pa + po, mul_bf16x2(pA[0], i0), mul_bf16x2(pA[1], i1), mul_bf16x2(pA[2], i2), mul_bf16x2(pA[3], i3));
        stsm_x4_t(pa + po + 128, mul_bf16x2(pB[0], i0), mul_bf16x2(pB[1], i1), mul_bf16x2(pB[2], i2), mul_bf16x2(pB[3], i3));
        stsm_x4_t(pa + (po + (8 - warp) * 128), mul_bf16x2(pC[0], i0), mul_bf16x2(pC[1], i1), mul_bf16x2(pC[2], i2), mul_bf16x2(pC[3], i3));
        stsm_x4_t(pd0, mul_bf16x2(pA[4], i4), mul_bf16x2(pB[4], i4), mul_bf16x2(pC[4], i4), mul_bf16x2(d0, id));
        if (warp == 3) stsm_x1_t(pd0 + 6 * 128, mul_bf16x2(d1, i4));
        bar_arrive(BAR_PF + (it & 1), 384);
        load_k(false, IC<4>{}, IC<4 + kRs>{});
      }
      finish(n_items);
    }
  }
}

typedef CUresult (*EncodeFn)(CUtensorMap*, CUtensorMapDataType, cuuint32_t, void*, const cuuint64_t*, const cuuint64_t*,
                             const cuuint32_t*, const cuuint32_t*, CUtensorMapInterleave, CUtensorMapSwizzle,
                             CUtensorMapL2promotion, CUtensorMapFloatOOBfill);

}

extern "C" void kernel_launch(void* const* d_in, const int* in_sizes, int n_in, void* d_out, int out_size) {
  static EncodeFn encode = nullptr;
  static int num_sms = 0;
  static unsigned* claim = nullptr;
  if (!encode) {
    void* fn = nullptr;
    cudaDriverEntryPointQueryResult qres;
    cudaGetDriverEntryPoint("cuTensorMapEncodeTiled", &fn, cudaEnableDefault, &qres);
    encode = (EncodeFn)fn;
    int dev = 0;
    cudaGetDevice(&dev);
    cudaDeviceGetAttribute(&num_sms, cudaDevAttrMultiProcessorCount, dev);
    cudaGetSymbolAddress((void**)&claim, g_claim);
    cudaFuncSetAttribute(autoint_kernel, cudaFuncAttributeMaxDynamicSharedMemorySize, kSmemBytes);
  }
  auto make = [&](void* p, uint64_t cols, uint64_t rows, uint32_t box_rows, CUtensorMapL2promotion promo) {
    CUtensorMap tm;
    cuuint64_t dims[2] = {cols, rows};
    cuuint64_t strides[1] = {cols * 2};
    cuuint32_t box[2] = {64, box_rows};
    cuuint32_t estr[2] = {1, 1};
    encode(&tm, CU_TENSOR_MAP_DATA_TYPE_BFLOAT16, 2, p, dims, strides, box, estr, CU_TENSOR_MAP_INTERLEAVE_NONE,
           CU_TENSOR_MAP_SWIZZLE_128B, promo, CU_TENSOR_MAP_FLOAT_OOB_FILL_NONE);
    return tm;
  };
  Maps tm;
  for (int i = 0; i < 2; i++) {
    cuuint64_t dims[3] = {64, (cuuint64_t)kB * kF, 2};
    cuuint64_t strides[2] = {kD * 2, 128};
    cuuint32_t box[3] = {64, i ? 96u : 104u, 2};
    cuuint32_t estr[3] = {1, 1, 1};
    encode(&tm.m[i], CU_TENSOR_MAP_DATA_TYPE_BFLOAT16, 3, d_in[0], dims, strides, box, estr, CU_TENSOR_MAP_INTERLEAVE_NONE,
           CU_TENSOR_MAP_SWIZZLE_128B, CU_TENSOR_MAP_L2_PROMOTION_L2_256B, CU_TENSOR_MAP_FLOAT_OOB_FILL_NONE);
  }
  tm.m[2] = make(d_out, kD, (uint64_t)kB * kF, kF, CU_TENSOR_MAP_L2_PROMOTION_NONE);
  for (int i = 0; i < 3; i++) tm.m[3 + i] = make(d_in[1 + i], 64, 256, 128, CU_TENSOR_MAP_L2_PROMOTION_L2_256B);
  tm.m[6] = make(d_in[4], 128, 128, 128, CU_TENSOR_MAP_L2_PROMOTION_L2_256B);
  tm.m[7] = make(d_in[0], kD, (uint64_t)kB * kF, 104, CU_TENSOR_MAP_L2_PROMOTION_L2_128B);
  const int grid = (num_sms < 2 ? 2 : num_sms > 256 ? 256 : num_sms) & ~1, streams = grid / 2;
  const int n_pairs = kB / 2 / streams, rem = kB / 2 - n_pairs * streams;
  const bool open = 2 * rem <= streams;
  Params prm;
  for (int i = 0; i < 4; i++) prm.w[i] = (const uint8_t*)d_in[1 + i];
  prm.out = (uint8_t*)d_out;
  prm.claim = claim;
  prm.n_pairs = (short)n_pairs;
  prm.n_extra = (short)(open ? 0 : rem);
  prm.n_open = (short)(open ? 2 * rem : 0);
  prm.streams = (short)streams;
  autoint_kernel<<<grid, 512, kSmemBytes>>>(prm, tm);
}
```
